```python
import torch

def _softmax(x, axis=-1):
    return torch.softmax(x, dim=axis)
def _gelu(x):
    return torch.nn.functional.gelu(x, approximate="tanh")
def _silu(x):
    return torch.nn.functional.silu(x)
def _sigmoid(x):
    return torch.sigmoid(x)
def _layernorm(x, axis=-1, eps=1e-5):
    m = x.mean(dim=axis, keepdim=True)
    v = x.var(dim=axis, keepdim=True, unbiased=False)
    return (x - m) / torch.sqrt(v + eps)
def _scatter_add(tgt, idx, src, axis=0):
    return tgt.clone().index_add_(axis, idx, src)
def _segment_sum(src, seg, n):
    out = torch.zeros((n,) + src.shape[1:], dtype=src.dtype)
    return out.index_add_(0, seg, src)
def _pad(x, pw):
    flat = tuple(v for pair in reversed(pw) for v in pair)
    return torch.nn.functional.pad(x, flat)

kernel_name = 'interleave_layers__spectral_gfnet__glu_gated_reglu__prompt'

def setup_inputs():

    _w = (lambda a: (lambda t: t.to(torch.bfloat16) if t.is_floating_point() else t)(torch.as_tensor(a)))
    def _A_setup():
        B, S, D = 1, 2048, 512
        Df = D // 2 + 1
        return {
            "x": _w((lambda *s: torch.randn(*s, dtype=torch.bfloat16) * 0.05)(B, S, D)),
            "w_r": _w((lambda *s: torch.randn(*s, dtype=torch.bfloat16) * 0.4)(S, Df) * 0.02),
            "w_i": _w((lambda *s: torch.randn(*s, dtype=torch.bfloat16) * 0.4)(S, Df) * 0.02),
        }
    _A_in = _A_setup()

    def _B_setup():
        B, S, D, F = 1, 2048, 512, 1792
        return {
            "x": _w((lambda *s: torch.randn(*s, dtype=torch.bfloat16) * 0.05)(B, S, D)),
            "W_gate": _w((lambda *s: torch.randn(*s, dtype=torch.bfloat16) * 0.2)(D, F) * (2.0 / D) ** 0.5),
            "W_up": _w((lambda *s: torch.randn(*s, dtype=torch.bfloat16) * 0.2)(D, F) * (2.0 / D) ** 0.5),
            "W_down": _w((lambda *s: torch.randn(*s, dtype=torch.bfloat16) * 0.2)(F, D) * (1.0 / F) ** 0.5),
        }
    _B_in = _B_setup()

    return {
        "A_x": _A_in["x"],
        "A_w_r": _A_in["w_r"],
        "A_w_i": _A_in["w_i"],
        "B_x": _B_in["x"],
        "B_W_gate": _B_in["W_gate"],
        "B_W_up": _B_in["W_up"],
        "B_W_down": _B_in["W_down"],
    }

def reference(A_x, A_w_r, A_w_i, B_x, B_W_gate, B_W_up, B_W_down):
    def _A_ref(x, w_r, w_i):
        B, S, D = x.shape
        X = (lambda x, axes=(-2,-1): torch.fft.rfft2(x.float(), dim=axes))(x, axes=(-2, -1))
        W = w_r + 1j * w_i
        X = X * W
        y = (lambda x, s, axes=(-2,-1): torch.fft.irfft2(x, s=s, dim=axes).to(torch.bfloat16))(X, (S, D), axes=(-2, -1))
        return y

    def _B_ref(x, W_gate, W_up, W_down):
        gate = torch.einsum("bsd,df->bsf", x, W_gate)
        up = torch.einsum("bsd,df->bsf", x, W_up)
        gate = gate * (lambda x, dt: x.to(dt))(gate > 0, gate.dtype)
        h = gate * up
        return torch.einsum("bsf,fd->bsd", h, W_down)

    x = A_x
    x = x + _A_ref(_layernorm(x, axis=-1), A_w_r, A_w_i)
    x = x + _B_ref(_layernorm(x, axis=-1), B_W_gate, B_W_up, B_W_down)
    x = x + _A_ref(_layernorm(x, axis=-1), A_w_r, A_w_i)
    x = x + _B_ref(_layernorm(x, axis=-1), B_W_gate, B_W_up, B_W_down)
    return x
```

```cpp
#include <cuda_runtime.h>
#include <cuda_bf16.h>
#include <cuda_fp16.h>
#include <cuda.h>
#include <stdint.h>

__device__ const __align__(128) uint32_t TAB_ALL[16384] = {
0x34003400,0x3400,0x34003400,0x8000b400,0x34003400,0xae1f3364,0x34003400,0x2e1fb364,0x34003400,0xb1a831a8,0x34003400,0x31a8b1a8,0x34003400,0xb3642e1f,0x34003400,0x3364ae1f,
0xb4003400,0x80003400,0xb4003400,0xb400,0xb1a831a8,0x33642e1f,0xb1a831a8,0xb364ae1f,0x80000000,0x31a8b1a8,0x80000000,0xb1a831a8,0x31a8b1a8,0xae1fb364,0x31a8b1a8,0x2e1f3364,
0x34003400,0x3400,0x34003400,0x8000b400,0x0,0xb364ae1f,0x0,0x33642e1f,0xb400b400,0x31a8b1a8,0xb400b400,0xb1a831a8,0x80008000,0x2e1f3364,0x80008000,0xae1fb364,
0xb4003400,0x80003400,0xb4003400,0xb400,0x31a8b1a8,0x2e1fb364,0x31a8b1a8,0xae1f3364,0x8000,0xb1a831a8,0x8000,0x31a8b1a8,0xb1a831a8,0x3364ae1f,0xb1a831a8,0xb3642e1f,
0x34003400,0x3400,0x34003400,0x8000b400,0xb400b400,0x2e1fb364,0xb400b400,0xae1f3364,0x34003400,0xb1a831a8,0x34003400,0x31a8b1a8,0xb400b400,0x3364ae1f,0xb400b400,0xb3642e1f,
0xb4003400,0x80003400,0xb4003400,0xb400,0x31a8b1a8,0xb364ae1f,0x31a8b1a8,0x33642e1f,0x80000000,0x31a8b1a8,0x80000000,0xb1a831a8,0xb1a831a8,0x2e1f3364,0xb1a831a8,0xae1fb364,
0x34003400,0x3400,0x34003400,0x8000b400,0x80008000,0x33642e1f,0x80008000,0xb364ae1f,0xb400b400,0x31a8b1a8,0xb400b400,0xb1a831a8,0x0,0xae1fb364,0x0,0x2e1f3364,
0xb4003400,0x80003400,0xb4003400,0xb400,0xb1a831a8,0xae1f3364,0xb1a831a8,0x2e1fb364,0x8000,0xb1a831a8,0x8000,0x31a8b1a8,0x31a8b1a8,0xb3642e1f,0x31a8b1a8,0x3364ae1f,
0x0,0xb4000000,0x0,0x34008000,0x0,0xb364ae1f,0x0,0x33642e1f,0x0,0xb1a8b1a8,0x0,0x31a831a8,0x0,0xae1fb364,0x0,0x2e1f3364,
0x80000000,0x34000000,0x80000000,0xb4008000,0x31a8b1a8,0x2e1fb364,0x31a8b1a8,0xae1f3364,0x3400b400,0xb1a8b1a8,0x3400b400,0x31a831a8,0x31a8b1a8,0xb3642e1f,0x31a8b1a8,0x3364ae1f,
0x0,0xb4000000,0x0,0x34008000,0xb400b400,0x2e1fb364,0xb400b400,0xae1f3364,0x80008000,0x31a831a8,0x80008000,0xb1a8b1a8,0x34003400,0xb3642e1f,0x34003400,0x3364ae1f,
0x80000000,0x34000000,0x80000000,0xb4008000,0x31a8b1a8,0xb364ae1f,0x31a8b1a8,0x33642e1f,0xb4003400,0x31a831a8,0xb4003400,0xb1a8b1a8,0x31a8b1a8,0xae1fb364,0x31a8b1a8,0x2e1f3364,
0x0,0xb4000000,0x0,0x34008000,0x80008000,0x33642e1f,0x80008000,0xb364ae1f,0x0,0xb1a8b1a8,0x0,0x31a831a8,0x80008000,0x2e1f3364,0x80008000,0xae1fb364,
0x80000000,0x34000000,0x80000000,0xb4008000,0xb1a831a8,0xae1f3364,0xb1a831a8,0x2e1fb364,0x3400b400,0xb1a8b1a8,0x3400b400,0x31a831a8,0xb1a831a8,0x3364ae1f,0xb1a831a8,0xb3642e1f,
0x0,0xb4000000,0x0,0x34008000,0x34003400,0xae1f3364,0x34003400,0x2e1fb364,0x80008000,0x31a831a8,0x80008000,0xb1a8b1a8,0xb400b400,0x3364ae1f,0xb400b400,0xb3642e1f,
0x80000000,0x34000000,0x80000000,0xb4008000,0xb1a831a8,0x33642e1f,0xb1a831a8,0xb364ae1f,0xb4003400,0x31a831a8,0xb4003400,0xb1a8b1a8,0xb1a831a8,0x2e1f3364,0xb1a831a8,0xae1fb364,
0x3c003c00,0x3bfe3c00,0x0,0xaa480000,0x3c003c00,0x3bea3bf6,0x0,0xb0b2ae46,0x3c003c00,0x3bc33bd9,0x0,0xb3c6b23e,0x3c003c00,0x3b883ba8,0x0,0xb564b4a5,
0x3bf63c00,0x3bea3c00,0xae460000,0xb0b20000,0x3ba83bd9,0x3b3b3ba8,0xb4a5b23e,0xb6d7b4a5,0x3b0e3b64,0x39ed3aa7,0xb78bb61f,0xb95fb872,0x3a2f3aa7,0x381d3913,0xb913b872,0xbaddba2f,
0x3bd93c00,0x3bc33c00,0xb23e0000,0xb3c60000,0x3aa73b64,0x39ed3b0e,0xb872b61f,0xb95fb78b,0x387239a8,0x35643872,0xbaa7b9a8,0xbb88baa7,0x323e361f,0xb0b22e46,0xbbd9bb64,0xbbeabbf6,
0x3ba83c00,0x3b883c00,0xb4a50000,0xb5640000,0x39133aa7,0x381d3a2f,0xba2fb872,0xbaddb913,0x2e46361f,0xb0b2323e,0xbbf6bb64,0xbbeabbd9,0xb78bb23e,0xb9edb78b,0xbb0ebbd9,0xb95fbb0e,
0x3b643c00,0x3b3b3c00,0xb61f0000,0xb6d70000,0x361f39a8,0x33c63913,0xbb64b9a8,0xbbc3ba2f,0xb61f0000,0xb8c4b23e,0xbb64bc00,0xba6dbbd9,0xbb64b9a8,0xbbfebb0e,0xb61fb9a8,0xaa48b78b,
0x3b0e3c00,0x3add3c00,0xb78b0000,0xb81d0000,0x2e463872,0xaa48378b,0xbbf6baa7,0xbbfebb0e,0xba2fb61f,0xbb3bb872,0xb913bb64,0xb6d7baa7,0xbba8bbd9,0xba6dbbf6,0x34a5b23e,0x38c42e46,
0x3aa73c00,0x3a6d3c00,0xb8720000,0xb8c40000,0xb23e361f,0xb56434a5,0xbbd9bb64,0xbb88bba8,0xbbd9b9a8,0xbbfebaa7,0xb23eb9a8,0x2a48b872,0xb872bb64,0xb3c6ba2f,0x3aa7361f,0x3bc33913,
0x3a2f3c00,0x39ed3c00,0xb9130000,0xb95f0000,0xb78b323e,0xb8c42e46,0xbb0ebbd9,0xba6dbbf6,0xbba8bb64,0xbaddbbd9,0x34a5b61f,0x381db23e,0x2e46b872,0x36d7b4a5,0x3bf63aa7,0x3b3b3ba8,
0x3c003c00,0x3bfc3c00,0x0,0xabd9a248,0x3c003c00,0x3be63bf4,0x0,0xb115af0e,0x3c003c00,0x3bbc3bd4,0x0,0xb414b2a1,0x3c003c00,0x3b803ba0,0x0,0xb593b4d5,
0x3bf13bff,0x3bdd3bff,0xafd6a648,0xb1dba8b6,0x3b993bce,0x3b1a3b91,0xb505b303,0xb75eb534,0x3af63b50,0x39ba3a7c,0xb7e3b67c,0xb996b8b0,0x3a0f3a8a,0x37b738d8,0xb93ab89b,0xbb02ba5e,
0x3bc33bfe,0x3ba03bfc,0xb3c6aa48,0xb4d5abd9,0x3a6d3b3b,0x39963ad0,0xb8c4b6d7,0xb9bab832,0x381d395f,0x34753807,0xbaddb9ed,0xbbafbae9,0x30b23564,0xb2a128b6,0xbbeabb88,0xbbd4bbff,
0x3b773bfa,0x3b463bf8,0xb5c2acb5,0xb6aaad7e,0x389b3a4f,0x370539ba,0xba8ab8ec,0xbb30b996,0x26483505,0xb3652f0e,0xbbffbb99,0xbbc9bbf4,0xb848b444,0xba5eb85d,0xbac2bbb6,0xb8d8bab5,
0x3b0e3bf6,0x3ad03bf4,0xb78bae46,0xb832af0e,0x34a53913,0x304e385d,0xbba8ba2f,0xbbedbab5,0xb78bae46,0xb972b4d5,0xbb0ebbf6,0xb9dcbba0,0xbba8ba2f,0xbbfcbb6e,0xb4a5b913,0x2bd9b5f1,
0x3a8a3bf1,0x3a3f3bed,0xb89bafd6,0xb900b04e,0xa6483732,0xb1db3593,0xbbffbb25,0xbbddbb80,0xbac2b7e3,0xbba0b94d,0xb848baf6,0xb4d5b9fe,0xbb50bbfa,0xb9babbc9,0x367cacb5,0x39963365,
0x39ed3bea,0x39963be6,0xb95fb0b2,0xb9bab115,0xb56433c6,0xb7b7304e,0xbb88bbc3,0xbb02bbed,0xbbfeba6d,0xbbd4bb46,0xaa48b8c4,0x32a1b6aa,0xb6d7badd,0xad7eb94d,0x3b3b381d,0x3bf839fe,
0x393a3be2,0x38d83bdd,0xba0fb179,0xba5eb1db,0xb8ec2648,0xb9dcad7e,0xba4fbbff,0xb972bbf8,0xbb25bbce,0xb9febc00,0x3732b303,0x394da248,0x3444b67c,0x38b0af0e,0x3bb63b50,0x3a7c3bf4,
0x3c003c00,0x3bfa3bff,0x0,0xacb5a648,0x3c003c00,0x3be23bf1,0x0,0xb179afd6,0x3c003c00,0x3bb63bce,0x0,0xb444b303,0x3c003c00,0x3b773b99,0x0,0xb5c2b505,
0x3bea3bfe,0x3bce3bfa,0xb0b2aa48,0xb303acb5,0x3b883bc3,0x3af63b77,0xb564b3c6,0xb7e3b5c2,0x3add3b3b,0x39843a4f,0xb81db6d7,0xb9cbb8ec,0x39ed3a6d,0x3732389b,0xb95fb8c4,0xbb25ba8a,
0x3ba83bf6,0x3b773bf1,0xb4a5ae46,0xb5c2afd6,0x3a2f3b0e,0x393a3a8a,0xb913b78b,0xba0fb89b,0x378b3913,0x33033732,0xbb0eba2f,0xbbcebb25,0x2e4634a5,0xb444a648,0xbbf6bba8,0xbbb6bbff,
0x3b3b3bea,0x3af63be2,0xb6d7b0b2,0xb7e3b179,0x381d39ed,0x35c2393a,0xbaddb95f,0xbb77ba0f,0xaa4833c6,0xb5052648,0xbbfebbc3,0xbb99bbff,0xb8c4b564,0xbac2b8ec,0xba6dbb88,0xb848ba4f,
0x3aa73bd9,0x3a4f3bce,0xb872b23e,0xb8ecb303,0x323e3872,0x26483732,0xbbd9baa7,0xbbffbb25,0xb872b23e,0xba0fb67c,0xbaa7bbd9,0xb93abb50,0xbbd9baa7,0xbbe2bbb6,0xb23eb872,0x3179b444,
0x39ed3bc3,0x39843bb6,0xb95fb3c6,0xb9cbb444,0xb0b23564,0xb5053303,0xbbeabb88,0xbb99bbce,0xbb3bb8c4,0xbbe2ba0f,0xb6d7ba6d,0xb179b93a,0xbaddbbfe,0xb8ecbb77,0x381d2a48,0x3a4f35c2,
0x39133ba8,0x389b3b99,0xba2fb4a5,0xba8ab505,0xb78b2e46,0xb8eca648,0xbb0ebbf6,0xba4fbbff,0xbbf6bb0e,0xbb77bbb6,0x2e46b78b,0x35c2b444,0xb4a5ba2f,0x2cb5b848,0x3ba83913,0x3bfa3ac2,
0x381d3b88,0x37323b77,0xbaddb564,0xbb25b5c2,0xb9edb0b2,0xbac2b444,0xb95fbbea,0xb848bbb6,0xba6dbbfe,0xb8ecbbe2,0x38c4aa48,0x3a4f3179,0x36d7b3c6,0x39cb2cb5,0x3b3b3bc3,0x39843bfa,
0x3c003c00,0x3bf83bff,0x0,0xad7ea8b6,0x3c003c00,0x3bdd3bed,0x0,0xb1dbb04e,0x3c003c00,0x3baf3bc9,0x0,0xb475b365,0x3c003c00,0x3b6e3b91,0x0,0xb5f1b534,
0x3be23bfa,0x3bbc3bf4,0xb179acb5,0xb414af0e,0x3b773bb6,0x3ad03b5a,0xb5c2b444,0xb832b64e,0x3ac23b25,0x394d3a1f,0xb848b732,0xb9feb927,0x39cb3a4f,0x36aa385d,0xb984b8ec,0xbb46bab5,
0x3b883bea,0x3b463bdd,0xb564b0b2,0xb6aab1db,0x39ed3add,0x38d83a3f,0xb95fb81d,0xba5eb900,0x36d738c4,0x3115364e,0xbb3bba6d,0xbbe6bb5a,0x2a4833c6,0xb534ad7e,0xbbfebbc3,0xbb91bbf8,
0x3af63bce,0x3a993bbc,0xb7e3b303,0xb887b414,0x37323984,0x347538b0,0xbb25b9cb,0xbbafba7c,0xafd63179,0xb64eabd9,0xbbf1bbe2,0xbb5abbfc,0xb93ab67c,0xbb1ab972,0xba0fbb50,0xb75eb9dc,
0x3a2f3ba8,0x39ba3b91,0xb913b4a5,0xb996b534,0x2e46378b,0xad7e3593,0xbbf6bb0e,0xbbf8bb80,0xb913b4a5,0xba99b807,0xba2fbba8,0xb887bae9,0xbbf6bb0e,0xbbafbbe6,0xae46b78b,0x3475b115,
0x393a3b77,0x38b03b5a,0xba0fb5c2,0xba7cb64e,0xb4443303,0xb7052d7e,0xbbb6bbce,0xbb30bbf8,0xbb99b984,0xbbffbab5,0xb505b9cb,0xa8b6b85d,0xba4fbbe2,0xb807bb02,0x38ec3179,0x3ae937b7,
0x381d3b3b,0x37053b1a,0xbaddb6d7,0xbb30b75e,0xb8c4aa48,0xb9dcb1db,0xba6dbbfe,0xb972bbdd,0xbbc3bb88,0xbae9bbf4,0x33c6b564,0x3807af0e,0xb0b2b95f,0x3365b64e,0x3bea39ed,0x3bc93b5a,
0x35c23af6,0x34753ad0,0xbb77b7e3,0xbbafb832,0xbac2b505,0xbb6eb705,0xb848bb99,0xb5f1bb30,0xb984bbf1,0xb75ebb80,0x39cb2fd6,0x3b1a3593,0x389bacb5,0x3ab53414,0x3a8a3bfa,0x385d3bbc,
0x34003400,0x80008000,0x0,0x34003400,0x34003400,0x80008000,0x0,0x34003400,0x34003400,0x80008000,0x0,0x34003400,0x34003400,0x80008000,0x0,0x34003400,
0x31a83400,0x31a88000,0xb1a80000,0x31a83400,0xb1a80000,0x31a83400,0xb1a8b400,0xb1a80000,0xb1a8b400,0xb1a80000,0x31a88000,0xb1a8b400,0x31a88000,0xb1a8b400,0x31a83400,0x31a88000,
0x3400,0x34008000,0xb4000000,0x3400,0x8000b400,0xb4000000,0x34008000,0x8000b400,0x3400,0x34008000,0xb4000000,0x3400,0x8000b400,0xb4000000,0x34008000,0x8000b400,
0xb1a83400,0x31a88000,0xb1a80000,0xb1a83400,0x31a88000,0x31a8b400,0xb1a83400,0x31a88000,0x31a8b400,0xb1a80000,0x31a88000,0x31a8b400,0xb1a80000,0xb1a83400,0x31a8b400,0xb1a80000,
0xb4003400,0x8000,0x80000000,0xb4003400,0xb4003400,0x8000,0x80000000,0xb4003400,0xb4003400,0x8000,0x80000000,0xb4003400,0xb4003400,0x8000,0x80000000,0xb4003400,
0xb1a83400,0xb1a88000,0x31a80000,0xb1a83400,0x31a80000,0xb1a83400,0x31a8b400,0x31a80000,0x31a8b400,0x31a80000,0xb1a88000,0x31a8b400,0xb1a88000,0x31a8b400,0xb1a83400,0xb1a88000,
0x80003400,0xb4008000,0x34000000,0x80003400,0xb400,0x34000000,0xb4008000,0xb400,0x80003400,0xb4008000,0x34000000,0x80003400,0xb400,0x34000000,0xb4008000,0xb400,
0x31a83400,0xb1a88000,0x31a80000,0x31a83400,0xb1a88000,0xb1a8b400,0x31a83400,0xb1a88000,0xb1a8b400,0x31a80000,0xb1a88000,0xb1a8b400,0x31a80000,0x31a83400,0xb1a8b400,0x31a80000,
0x34003400,0x80008000,0x0,0x34003400,0x34003400,0x80008000,0x0,0x34003400,0x34003400,0x80008000,0x0,0x34003400,0x34003400,0x80008000,0x0,0x34003400,
0x31a83400,0x31a88000,0xb1a80000,0x31a83400,0xb1a80000,0x31a83400,0xb1a8b400,0xb1a80000,0xb1a8b400,0xb1a80000,0x31a88000,0xb1a8b400,0x31a88000,0xb1a8b400,0x31a83400,0x31a88000,
0x3400,0x34008000,0xb4000000,0x3400,0x8000b400,0xb4000000,0x34008000,0x8000b400,0x3400,0x34008000,0xb4000000,0x3400,0x8000b400,0xb4000000,0x34008000,0x8000b400,
0xb1a83400,0x31a88000,0xb1a80000,0xb1a83400,0x31a88000,0x31a8b400,0xb1a83400,0x31a88000,0x31a8b400,0xb1a80000,0x31a88000,0x31a8b400,0xb1a80000,0xb1a83400,0x31a8b400,0xb1a80000,
0xb4003400,0x8000,0x80000000,0xb4003400,0xb4003400,0x8000,0x80000000,0xb4003400,0xb4003400,0x8000,0x80000000,0xb4003400,0xb4003400,0x8000,0x80000000,0xb4003400,
0xb1a83400,0xb1a88000,0x31a80000,0xb1a83400,0x31a80000,0xb1a83400,0x31a8b400,0x31a80000,0x31a8b400,0x31a80000,0xb1a88000,0x31a8b400,0xb1a88000,0x31a8b400,0xb1a83400,0xb1a88000,
0x80003400,0xb4008000,0x34000000,0x80003400,0xb400,0x34000000,0xb4008000,0xb400,0x80003400,0xb4008000,0x34000000,0x80003400,0xb400,0x34000000,0xb4008000,0xb400,
0x31a83400,0xb1a88000,0x31a80000,0x31a83400,0xb1a88000,0xb1a8b400,0x31a83400,0xb1a88000,0xb1a8b400,0x31a80000,0xb1a88000,0xb1a8b400,0x31a80000,0x31a83400,0xb1a8b400,0x31a80000,
0x34003400,0x80008000,0x0,0x34003400,0x34003400,0x80008000,0x0,0x34003400,0x34003400,0x80008000,0x0,0x34003400,0x34003400,0x80008000,0x0,0x34003400,
0x307233d9,0x32a72a3e,0xb2a7aa3e,0x307233d9,0xb2a7aa3e,0x307233d9,0xb072b3d9,0xb2a7aa3e,0xb072b3d9,0xb2a7aa3e,0x32a72a3e,0xb072b3d9,0x32a72a3e,0xb072b3d9,0x307233d9,0x32a72a3e,
0xae1f3364,0x33642e1f,0xb364ae1f,0xae1f3364,0x2e1fb364,0xb364ae1f,0x33642e1f,0x2e1fb364,0xae1f3364,0x33642e1f,0xb364ae1f,0xae1f3364,0x2e1fb364,0xb364ae1f,0x33642e1f,0x2e1fb364,
0xb3d932a7,0x2a3e3072,0xaa3eb072,0xb3d932a7,0x2a3e3072,0x33d9b2a7,0xb3d932a7,0x2a3e3072,0x33d9b2a7,0xaa3eb072,0x2a3e3072,0x33d9b2a7,0xaa3eb072,0xb3d932a7,0x33d9b2a7,0xaa3eb072,
0xb1a831a8,0xb1a831a8,0x31a8b1a8,0xb1a831a8,0xb1a831a8,0xb1a831a8,0x31a8b1a8,0xb1a831a8,0xb1a831a8,0xb1a831a8,0x31a8b1a8,0xb1a831a8,0xb1a831a8,0xb1a831a8,0x31a8b1a8,0xb1a831a8,
0x2a3e3072,0xb3d932a7,0x33d9b2a7,0x2a3e3072,0x33d9b2a7,0x2a3e3072,0xaa3eb072,0x33d9b2a7,0xaa3eb072,0x33d9b2a7,0xb3d932a7,0xaa3eb072,0xb3d932a7,0xaa3eb072,0x2a3e3072,0xb3d932a7,
0x33642e1f,0xae1f3364,0x2e1fb364,0x33642e1f,0xb364ae1f,0x2e1fb364,0xae1f3364,0xb364ae1f,0x33642e1f,0xae1f3364,0x2e1fb364,0x33642e1f,0xb364ae1f,0x2e1fb364,0xae1f3364,0xb364ae1f,
0x32a72a3e,0x307233d9,0xb072b3d9,0x32a72a3e,0x307233d9,0xb2a7aa3e,0x32a72a3e,0x307233d9,0xb2a7aa3e,0xb072b3d9,0x307233d9,0xb2a7aa3e,0xb072b3d9,0x32a72a3e,0xb2a7aa3e,0xb072b3d9,
0x0,0x34003400,0xb400b400,0x0,0x0,0x34003400,0xb400b400,0x0,0x0,0x34003400,0xb400b400,0x0,0x0,0x34003400,0xb400b400,0x0,
0xb2a7aa3e,0x307233d9,0xb072b3d9,0xb2a7aa3e,0xb072b3d9,0xb2a7aa3e,0x32a72a3e,0xb072b3d9,0x32a72a3e,0xb072b3d9,0x307233d9,0x32a72a3e,0x307233d9,0x32a72a3e,0xb2a7aa3e,0x307233d9,
0xb364ae1f,0xae1f3364,0x2e1fb364,0xb364ae1f,0x33642e1f,0x2e1fb364,0xae1f3364,0x33642e1f,0xb364ae1f,0xae1f3364,0x2e1fb364,0xb364ae1f,0x33642e1f,0x2e1fb364,0xae1f3364,0x33642e1f,
0xaa3eb072,0xb3d932a7,0x33d9b2a7,0xaa3eb072,0xb3d932a7,0x2a3e3072,0xaa3eb072,0xb3d932a7,0x2a3e3072,0x33d9b2a7,0xb3d932a7,0x2a3e3072,0x33d9b2a7,0xaa3eb072,0x2a3e3072,0x33d9b2a7,
0x31a8b1a8,0xb1a831a8,0x31a8b1a8,0x31a8b1a8,0x31a8b1a8,0xb1a831a8,0x31a8b1a8,0x31a8b1a8,0x31a8b1a8,0xb1a831a8,0x31a8b1a8,0x31a8b1a8,0x31a8b1a8,0xb1a831a8,0x31a8b1a8,0x31a8b1a8,
0x33d9b2a7,0x2a3e3072,0xaa3eb072,0x33d9b2a7,0xaa3eb072,0x33d9b2a7,0xb3d932a7,0xaa3eb072,0xb3d932a7,0xaa3eb072,0x2a3e3072,0xb3d932a7,0x2a3e3072,0xb3d932a7,0x33d9b2a7,0x2a3e3072,
0x2e1fb364,0x33642e1f,0xb364ae1f,0x2e1fb364,0xae1f3364,0xb364ae1f,0x33642e1f,0xae1f3364,0x2e1fb364,0x33642e1f,0xb364ae1f,0x2e1fb364,0xae1f3364,0xb364ae1f,0x33642e1f,0xae1f3364,
0xb072b3d9,0x32a72a3e,0xb2a7aa3e,0xb072b3d9,0x32a72a3e,0x307233d9,0xb072b3d9,0x32a72a3e,0x307233d9,0xb2a7aa3e,0x32a72a3e,0x307233d9,0xb2a7aa3e,0xb072b3d9,0x307233d9,0xb2a7aa3e,
0x34003400,0x80008000,0x0,0x34003400,0x34003400,0x80008000,0x0,0x34003400,0x34003400,0x80008000,0x0,0x34003400,0x34003400,0x80008000,0x0,0x34003400,
0x2e1f3364,0x33642e1f,0xb364ae1f,0x2e1f3364,0xb364ae1f,0x2e1f3364,0xae1fb364,0xb364ae1f,0xae1fb364,0xb364ae1f,0x33642e1f,0xae1fb364,0x33642e1f,0xae1fb364,0x2e1f3364,0x33642e1f,
0xb1a831a8,0x31a831a8,0xb1a8b1a8,0xb1a831a8,0x31a8b1a8,0xb1a8b1a8,0x31a831a8,0x31a8b1a8,0xb1a831a8,0x31a831a8,0xb1a8b1a8,0xb1a831a8,0x31a8b1a8,0xb1a8b1a8,0x31a831a8,0x31a8b1a8,
0xb3642e1f,0xae1f3364,0x2e1fb364,0xb3642e1f,0xae1f3364,0x3364ae1f,0xb3642e1f,0xae1f3364,0x3364ae1f,0x2e1fb364,0xae1f3364,0x3364ae1f,0x2e1fb364,0xb3642e1f,0x3364ae1f,0x2e1fb364,
0x80000000,0xb4003400,0x3400b400,0x80000000,0x80000000,0xb4003400,0x3400b400,0x80000000,0x80000000,0xb4003400,0x3400b400,0x80000000,0x80000000,0xb4003400,0x3400b400,0x80000000,
0x3364ae1f,0xae1f3364,0x2e1fb364,0x3364ae1f,0x2e1fb364,0x3364ae1f,0xb3642e1f,0x2e1fb364,0xb3642e1f,0x2e1fb364,0xae1f3364,0xb3642e1f,0xae1f3364,0xb3642e1f,0x3364ae1f,0xae1f3364,
0x31a8b1a8,0x31a831a8,0xb1a8b1a8,0x31a8b1a8,0xb1a831a8,0xb1a8b1a8,0x31a831a8,0xb1a831a8,0x31a8b1a8,0x31a831a8,0xb1a8b1a8,0x31a8b1a8,0xb1a831a8,0xb1a8b1a8,0x31a831a8,0xb1a831a8,
0xae1fb364,0x33642e1f,0xb364ae1f,0xae1fb364,0x33642e1f,0x2e1f3364,0xae1fb364,0x33642e1f,0x2e1f3364,0xb364ae1f,0x33642e1f,0x2e1f3364,0xb364ae1f,0xae1fb364,0x2e1f3364,0xb364ae1f,
0xb400b400,0x0,0x80008000,0xb400b400,0xb400b400,0x0,0x80008000,0xb400b400,0xb400b400,0x0,0x80008000,0xb400b400,0xb400b400,0x0,0x80008000,0xb400b400,
0xae1fb364,0xb364ae1f,0x33642e1f,0xae1fb364,0x33642e1f,0xae1fb364,0x2e1f3364,0x33642e1f,0x2e1f3364,0x33642e1f,0xb364ae1f,0x2e1f3364,0xb364ae1f,0x2e1f3364,0xae1fb364,0xb364ae1f,
0x31a8b1a8,0xb1a8b1a8,0x31a831a8,0x31a8b1a8,0xb1a831a8,0x31a831a8,0xb1a8b1a8,0xb1a831a8,0x31a8b1a8,0xb1a8b1a8,0x31a831a8,0x31a8b1a8,0xb1a831a8,0x31a831a8,0xb1a8b1a8,0xb1a831a8,
0x3364ae1f,0x2e1fb364,0xae1f3364,0x3364ae1f,0x2e1fb364,0xb3642e1f,0x3364ae1f,0x2e1fb364,0xb3642e1f,0xae1f3364,0x2e1fb364,0xb3642e1f,0xae1f3364,0x3364ae1f,0xb3642e1f,0xae1f3364,
0x8000,0x3400b400,0xb4003400,0x8000,0x8000,0x3400b400,0xb4003400,0x8000,0x8000,0x3400b400,0xb4003400,0x8000,0x8000,0x3400b400,0xb4003400,0x8000,
0xb3642e1f,0x2e1fb364,0xae1f3364,0xb3642e1f,0xae1f3364,0xb3642e1f,0x3364ae1f,0xae1f3364,0x3364ae1f,0xae1f3364,0x2e1fb364,0x3364ae1f,0x2e1fb364,0x3364ae1f,0xb3642e1f,0x2e1fb364,
0xb1a831a8,0xb1a8b1a8,0x31a831a8,0xb1a831a8,0x31a8b1a8,0x31a831a8,0xb1a8b1a8,0x31a8b1a8,0xb1a831a8,0xb1a8b1a8,0x31a831a8,0xb1a831a8,0x31a8b1a8,0x31a831a8,0xb1a8b1a8,0x31a8b1a8,
0x2e1f3364,0xb364ae1f,0x33642e1f,0x2e1f3364,0xb364ae1f,0xae1fb364,0x2e1f3364,0xb364ae1f,0xae1fb364,0x33642e1f,0xb364ae1f,0xae1fb364,0x33642e1f,0x2e1f3364,0xae1fb364,0x33642e1f,
0x34003400,0x80008000,0x0,0x34003400,0x34003400,0x80008000,0x0,0x34003400,0x34003400,0x80008000,0x0,0x34003400,0x34003400,0x80008000,0x0,0x34003400,
0x2a3e32a7,0x33d93072,0xb3d9b072,0x2a3e32a7,0xb3d9b072,0x2a3e32a7,0xaa3eb2a7,0xb3d9b072,0xaa3eb2a7,0xb3d9b072,0x33d93072,0xaa3eb2a7,0x33d93072,0xaa3eb2a7,0x2a3e32a7,0x33d93072,
0xb3642e1f,0x2e1f3364,0xae1fb364,0xb3642e1f,0x3364ae1f,0xae1fb364,0x2e1f3364,0x3364ae1f,0xb3642e1f,0x2e1f3364,0xae1fb364,0xb3642e1f,0x3364ae1f,0xae1fb364,0x2e1f3364,0x3364ae1f,
0xb072aa3e,0xb2a733d9,0x32a7b3d9,0xb072aa3e,0xb2a733d9,0x30722a3e,0xb072aa3e,0xb2a733d9,0x30722a3e,0x32a7b3d9,0xb2a733d9,0x30722a3e,0x32a7b3d9,0xb072aa3e,0x30722a3e,0x32a7b3d9,
0x31a8b1a8,0xb1a831a8,0x31a8b1a8,0x31a8b1a8,0x31a8b1a8,0xb1a831a8,0x31a8b1a8,0x31a8b1a8,0x31a8b1a8,0xb1a831a8,0x31a8b1a8,0x31a8b1a8,0x31a8b1a8,0xb1a831a8,0x31a8b1a8,0x31a8b1a8,
0x32a7b3d9,0x30722a3e,0xb072aa3e,0x32a7b3d9,0xb072aa3e,0x32a7b3d9,0xb2a733d9,0xb072aa3e,0xb2a733d9,0xb072aa3e,0x30722a3e,0xb2a733d9,0x30722a3e,0xb2a733d9,0x32a7b3d9,0x30722a3e,
0xae1fb364,0x3364ae1f,0xb3642e1f,0xae1fb364,0x2e1f3364,0xb3642e1f,0x3364ae1f,0x2e1f3364,0xae1fb364,0x3364ae1f,0xb3642e1f,0xae1fb364,0x2e1f3364,0xb3642e1f,0x3364ae1f,0x2e1f3364,
0xb3d9b072,0xaa3eb2a7,0x2a3e32a7,0xb3d9b072,0xaa3eb2a7,0x33d93072,0xb3d9b072,0xaa3eb2a7,0x33d93072,0x2a3e32a7,0xaa3eb2a7,0x33d93072,0x2a3e32a7,0xb3d9b072,0x33d93072,0x2a3e32a7,
0x80008000,0xb400b400,0x34003400,0x80008000,0x80008000,0xb400b400,0x34003400,0x80008000,0x80008000,0xb400b400,0x34003400,0x80008000,0x80008000,0xb400b400,0x34003400,0x80008000,
0x33d93072,0xaa3eb2a7,0x2a3e32a7,0x33d93072,0x2a3e32a7,0x33d93072,0xb3d9b072,0x2a3e32a7,0xb3d9b072,0x2a3e32a7,0xaa3eb2a7,0xb3d9b072,0xaa3eb2a7,0xb3d9b072,0x33d93072,0xaa3eb2a7,
0x2e1f3364,0x3364ae1f,0xb3642e1f,0x2e1f3364,0xae1fb364,0xb3642e1f,0x3364ae1f,0xae1fb364,0x2e1f3364,0x3364ae1f,0xb3642e1f,0x2e1f3364,0xae1fb364,0xb3642e1f,0x3364ae1f,0xae1fb364,
0xb2a733d9,0x30722a3e,0xb072aa3e,0xb2a733d9,0x30722a3e,0x32a7b3d9,0xb2a733d9,0x30722a3e,0x32a7b3d9,0xb072aa3e,0x30722a3e,0x32a7b3d9,0xb072aa3e,0xb2a733d9,0x32a7b3d9,0xb072aa3e,
0xb1a831a8,0xb1a831a8,0x31a8b1a8,0xb1a831a8,0xb1a831a8,0xb1a831a8,0x31a8b1a8,0xb1a831a8,0xb1a831a8,0xb1a831a8,0x31a8b1a8,0xb1a831a8,0xb1a831a8,0xb1a831a8,0x31a8b1a8,0xb1a831a8,
0x30722a3e,0xb2a733d9,0x32a7b3d9,0x30722a3e,0x32a7b3d9,0x30722a3e,0xb072aa3e,0x32a7b3d9,0xb072aa3e,0x32a7b3d9,0xb2a733d9,0xb072aa3e,0xb2a733d9,0xb072aa3e,0x30722a3e,0xb2a733d9,
0x3364ae1f,0x2e1f3364,0xae1fb364,0x3364ae1f,0xb3642e1f,0xae1fb364,0x2e1f3364,0xb3642e1f,0x3364ae1f,0x2e1f3364,0xae1fb364,0x3364ae1f,0xb3642e1f,0xae1fb364,0x2e1f3364,0xb3642e1f,
0xaa3eb2a7,0x33d93072,0xb3d9b072,0xaa3eb2a7,0x33d93072,0x2a3e32a7,0xaa3eb2a7,0x33d93072,0x2a3e32a7,0xb3d9b072,0x33d93072,0x2a3e32a7,0xb3d9b072,0xaa3eb2a7,0x2a3e32a7,0xb3d9b072,
0x34003400,0x31a83400,0x34003400,0xb1a80000,0x34003400,0x2e1f3364,0x34003400,0xb364ae1f,0x34003400,0xb1a8b400,0x34003400,0x31a88000,0x34003400,0xae1fb364,0x34003400,0x33642e1f,
0x3400,0xb1a83400,0x8000b400,0x31a88000,0xb1a831a8,0xb3642e1f,0x31a8b1a8,0xae1f3364,0x3400,0x31a8b400,0x8000b400,0xb1a80000,0xb1a831a8,0x3364ae1f,0x31a8b1a8,0x2e1fb364,
0xb4003400,0xb1a83400,0xb4003400,0x31a80000,0x80000000,0x3364ae1f,0x80000000,0x2e1fb364,0xb4003400,0x31a8b400,0xb4003400,0xb1a88000,0x80000000,0xb3642e1f,0x80000000,0xae1f3364,
0x80003400,0x31a83400,0xb400,0xb1a88000,0x31a8b1a8,0xae1fb364,0xb1a831a8,0x33642e1f,0x80003400,0xb1a8b400,0xb400,0x31a80000,0x31a8b1a8,0x2e1f3364,0xb1a831a8,0xb364ae1f,
0x34003400,0x31a83400,0x34003400,0xb1a80000,0xb400b400,0xae1fb364,0xb400b400,0x33642e1f,0x34003400,0xb1a8b400,0x34003400,0x31a88000,0xb400b400,0x2e1f3364,0xb400b400,0xb364ae1f,
0x3400,0xb1a83400,0x8000b400,0x31a88000,0x31a8b1a8,0x3364ae1f,0xb1a831a8,0x2e1fb364,0x3400,0x31a8b400,0x8000b400,0xb1a80000,0x31a8b1a8,0xb3642e1f,0xb1a831a8,0xae1f3364,
0xb4003400,0xb1a83400,0xb4003400,0x31a80000,0x8000,0xb3642e1f,0x8000,0xae1f3364,0xb4003400,0x31a8b400,0xb4003400,0xb1a88000,0x8000,0x3364ae1f,0x8000,0x2e1fb364,
0x80003400,0x31a83400,0xb400,0xb1a88000,0xb1a831a8,0x2e1f3364,0x31a8b1a8,0xb364ae1f,0x80003400,0xb1a8b400,0xb400,0x31a80000,0xb1a831a8,0xae1fb364,0x31a8b1a8,0x33642e1f,
0x0,0xb1a80000,0x0,0xb1a8b400,0x0,0xb364ae1f,0x0,0xae1fb364,0x0,0x31a88000,0x0,0x31a83400,0x0,0x33642e1f,0x0,0x2e1f3364,
0xb4000000,0xb1a80000,0x34008000,0xb1a83400,0xb1a8b1a8,0x2e1fb364,0x31a831a8,0xb3642e1f,0xb4000000,0x31a88000,0x34008000,0x31a8b400,0xb1a8b1a8,0xae1f3364,0x31a831a8,0x3364ae1f,
0x80000000,0x31a80000,0x80000000,0x31a8b400,0x3400b400,0x2e1fb364,0x3400b400,0xb3642e1f,0x80000000,0xb1a88000,0x80000000,0xb1a83400,0x3400b400,0xae1f3364,0x3400b400,0x3364ae1f,
0x34000000,0x31a80000,0xb4008000,0x31a83400,0xb1a8b1a8,0xb364ae1f,0x31a831a8,0xae1fb364,0x34000000,0xb1a88000,0xb4008000,0xb1a8b400,0xb1a8b1a8,0x33642e1f,0x31a831a8,0x2e1f3364,
0x0,0xb1a80000,0x0,0xb1a8b400,0x80008000,0x33642e1f,0x80008000,0x2e1f3364,0x0,0x31a88000,0x0,0x31a83400,0x80008000,0xb364ae1f,0x80008000,0xae1fb364,
0xb4000000,0xb1a80000,0x34008000,0xb1a83400,0x31a831a8,0xae1f3364,0xb1a8b1a8,0x3364ae1f,0xb4000000,0x31a88000,0x34008000,0x31a8b400,0x31a831a8,0x2e1fb364,0xb1a8b1a8,0xb3642e1f,
0x80000000,0x31a80000,0x80000000,0x31a8b400,0xb4003400,0xae1f3364,0xb4003400,0x3364ae1f,0x80000000,0xb1a88000,0x80000000,0xb1a83400,0xb4003400,0x2e1fb364,0xb4003400,0xb3642e1f,
0x34000000,0x31a80000,0xb4008000,0x31a83400,0x31a831a8,0x33642e1f,0xb1a8b1a8,0x2e1f3364,0x34000000,0xb1a88000,0xb4008000,0xb1a8b400,0x31a831a8,0xb364ae1f,0xb1a8b1a8,0xae1fb364,
0x3c003c00,0x3bff3c00,0x0,0xa6480000,0x3c003c00,0x3bfa3bfe,0x0,0xacb5aa48,0x3c003c00,0x3bce3bd9,0x0,0xb303b23e,0x3c003c00,0x3bb63bc3,0x0,0xb444b3c6,
0x3bfe3c00,0x3bfa3c00,0xaa480000,0xacb50000,0x3bea3bf6,0x3bce3bea,0xb0b2ae46,0xb303b0b2,0x3b3b3b64,0x3a4f3aa7,0xb6d7b61f,0xb8ecb872,0x3add3b0e,0x398439ed,0xb81db78b,0xb9cbb95f,
0x3bf63c00,0x3bf13c00,0xae460000,0xafd60000,0x3ba83bd9,0x3b773bc3,0xb4a5b23e,0xb5c2b3c6,0x391339a8,0x37323872,0xba2fb9a8,0xbb25baa7,0x378b3872,0x33033564,0xbb0ebaa7,0xbbcebb88,
0x3bea3c00,0x3be23c00,0xb0b20000,0xb1790000,0x3b3b3ba8,0x3af63b88,0xb6d7b4a5,0xb7e3b564,0x33c6361f,0x2648323e,0xbbc3bb64,0xbbffbbd9,0xaa482e46,0xb505b0b2,0xbbfebbf6,0xbb99bbea,
0x3bd93c00,0x3bce3c00,0xb23e0000,0xb3030000,0x3aa73b64,0x3a4f3b3b,0xb872b61f,0xb8ecb6d7,0xb23e0000,0xb67cb23e,0xbbd9bc00,0xbb50bbd9,0xb872b61f,0xba0fb8c4,0xbaa7bb64,0xb93aba6d,
0x3bc33c00,0x3bb63c00,0xb3c60000,0xb4440000,0x39ed3b0e,0x39843add,0xb95fb78b,0xb9cbb81d,0xb8c4b61f,0xba0fb872,0xba6dbb64,0xb93abaa7,0xbb3bba2f,0xbbe2bb3b,0xb6d7b913,0xb179b6d7,
0x3ba83c00,0x3b993c00,0xb4a50000,0xb5050000,0x39133aa7,0x389b3a6d,0xba2fb872,0xba8ab8c4,0xbb0eb9a8,0xbbb6baa7,0xb78bb9a8,0xb444b872,0xbbf6bbd9,0xbb77bbfe,0x2e46b23e,0x35c22a48,
0x3b883c00,0x3b773c00,0xb5640000,0xb5c20000,0x381d3a2f,0x373239ed,0xbaddb913,0xbb25b95f,0xbbfebb64,0xbbe2bbd9,0xaa48b61f,0x3179b23e,0xba6dbba8,0xb8ecbadd,0x38c434a5,0x3a4f381d,
0x3c003c00,0x3bff3c00,0x0,0xa8b6a248,0x3c003c00,0x3bf83bfc,0x0,0xad7eabd9,0x3c003c00,0x3bc93bd4,0x0,0xb365b2a1,0x3c003c00,0x3baf3bbc,0x0,0xb475b414,
0x3bfa3bff,0x3bf43bff,0xacb5a648,0xaf0ea8b6,0x3be23bf1,0x3bbc3bdd,0xb179afd6,0xb414b1db,0x3b253b50,0x3a1f3a7c,0xb732b67c,0xb927b8b0,0x3ac23af6,0x394d39ba,0xb848b7e3,0xb9feb996,
0x3bea3bfe,0x3bdd3bfc,0xb0b2aa48,0xb1dbabd9,0x3b883bc3,0x3b463ba0,0xb564b3c6,0xb6aab4d5,0x38c4395f,0x364e3807,0xba6db9ed,0xbb5abae9,0x36d7381d,0x31153475,0xbb3bbadd,0xbbe6bbaf,
0x3bce3bfa,0x3bbc3bf8,0xb303acb5,0xb414ad7e,0x3af63b77,0x3a993b46,0xb7e3b5c2,0xb887b6aa,0x31793505,0xabd92f0e,0xbbe2bb99,0xbbfcbbf4,0xafd62648,0xb64eb365,0xbbf1bbff,0xbb5abbc9,
0x3ba83bf6,0x3b913bf4,0xb4a5ae46,0xb534af0e,0x3a2f3b0e,0x39ba3ad0,0xb913b78b,0xb996b832,0xb4a5ae46,0xb807b4d5,0xbba8bbf6,0xbae9bba0,0xb913b78b,0xba99b972,0xba2fbb0e,0xb887b9dc,
0x3b773bf1,0x3b5a3bed,0xb5c2afd6,0xb64eb04e,0x393a3a8a,0x38b03a3f,0xba0fb89b,0xba7cb900,0xb984b7e3,0xbab5b94d,0xb9cbbaf6,0xb85db9fe,0xbb99bac2,0xbbffbba0,0xb505b848,0xa8b6b4d5,
0x3b3b3bea,0x3b1a3be6,0xb6d7b0b2,0xb75eb115,0x381d39ed,0x37053996,0xbaddb95f,0xbb30b9ba,0xbb88ba6d,0xbbf4bb46,0xb564b8c4,0xaf0eb6aa,0xbbc3bbfe,0xbae9bbd4,0x33c6aa48,0x380732a1,
0x3af63be2,0x3ad03bdd,0xb7e3b179,0xb832b1db,0x35c2393a,0x347538d8,0xbb77ba0f,0xbbafba5e,0xbbf1bbce,0xbb80bc00,0x2fd6b303,0x3593a248,0xb984bb25,0xb75eb9fe,0x39cb3732,0x3b1a394d,
0x3c003c00,0x3bf13bf6,0x0,0xafd6ae46,0x3c003c00,0x3be23bea,0x0,0xb179b0b2,0x3c003c00,0x3b993ba8,0x0,0xb505b4a5,0x3c003c00,0x3b773b88,0x0,0xb5c2b564,
0x3bc33bd9,0x3b773ba8,0xb3c6b23e,0xb5c2b4a5,0x3b883ba8,0x3af63b3b,0xb564b4a5,0xb7e3b6d7,0x3a6d3aa7,0x389b3913,0xb8c4b872,0xba8aba2f,0x39ed3a2f,0x3732381d,0xb95fb913,0xbb25badd,
0x3b0e3b64,0x3a8a3b0e,0xb78bb61f,0xb89bb78b,0x3a2f3aa7,0x393a39ed,0xb913b872,0xba0fb95f,0x34a5361f,0xa6482e46,0xbba8bb64,0xbbffbbf6,0x2e46323e,0xb444b0b2,0xbbf6bbd9,0xbbb6bbea,
0x39ed3aa7,0x393a3a2f,0xb95fb872,0xba0fb913,0x381d3913,0x35c2381d,0xbaddba2f,0xbb77badd,0xb564b23e,0xb8ecb78b,0xbb88bbd9,0xba4fbb0e,0xb8c4b78b,0xbac2b9ed,0xba6dbb0e,0xb848b95f,
0x387239a8,0x37323913,0xbaa7b9a8,0xbb25ba2f,0x323e361f,0x264833c6,0xbbd9bb64,0xbbffbbc3,0xbaa7b9a8,0xbbb6bb0e,0xb872b9a8,0xb444b78b,0xbbd9bb64,0xbbe2bbfe,0xb23eb61f,0x3179aa48,
0x35643872,0x3303378b,0xbb88baa7,0xbbcebb0e,0xb0b22e46,0xb505aa48,0xbbeabbf6,0xbb99bbfe,0xbbfebbd9,0xbb77bbf6,0x2a48b23e,0x35c22e46,0xbaddbba8,0xb8ecba6d,0x381d34a5,0x3a4f38c4,
0x2e46361f,0xa64834a5,0xbbf6bb64,0xbbffbba8,0xb78bb23e,0xb8ecb564,0xbb0ebbd9,0xba4fbb88,0xba2fbb64,0xb848ba2f,0x3913361f,0x3ac23913,0xb4a5b872,0x2cb5b3c6,0x3ba83aa7,0x3bfa3bc3,
0xb0b2323e,0xb4442e46,0xbbeabbd9,0xbbb6bbf6,0xb9edb78b,0xbac2b8c4,0xb95fbb0e,0xb848ba6d,0xb3c6b872,0x2cb5b4a5,0x3bc33aa7,0x3bfa3ba8,0x36d72e46,0x39cb36d7,0x3b3b3bf6,0x39843b3b,
0x3c003c00,0x3bed3bf4,0x0,0xb04eaf0e,0x3c003c00,0x3bdd3be6,0x0,0xb1dbb115,0x3c003c00,0x3b913ba0,0x0,0xb534b4d5,0x3c003c00,0x3b6e3b80,0x0,0xb5f1b593,
0x3bb63bce,0x3b5a3b91,0xb444b303,0xb64eb534,0x3b773b99,0x3ad03b1a,0xb5c2b505,0xb832b75e,0x3a4f3a8a,0x385d38d8,0xb8ecb89b,0xbab5ba5e,0x39cb3a0f,0x36aa37b7,0xb984b93a,0xbb46bb02,
0x3add3b3b,0x3a3f3ad0,0xb81db6d7,0xb900b832,0x39ed3a6d,0x38d83996,0xb95fb8c4,0xba5eb9ba,0x33c63564,0xad7e28b6,0xbbc3bb88,0xbbf8bbff,0x2a4830b2,0xb534b2a1,0xbbfebbea,0xbb91bbd4,
0x39843a4f,0x38b039ba,0xb9cbb8ec,0xba7cb996,0x3732389b,0x34753705,0xbb25ba8a,0xbbafbb30,0xb67cb444,0xb972b85d,0xbb50bbb6,0xb9dcbab5,0xb93ab848,0xbb1aba5e,0xba0fbac2,0xb75eb8d8,
0x378b3913,0x3593385d,0xbb0eba2f,0xbb80bab5,0x2e4634a5,0xad7e304e,0xbbf6bba8,0xbbf8bbed,0xbb0eba2f,0xbbe6bb6e,0xb78bb913,0xb115b5f1,0xbbf6bba8,0xbbafbbfc,0xae46b4a5,0x34752bd9,
0x33033732,0x2d7e3593,0xbbcebb25,0xbbf8bb80,0xb444a648,0xb705b1db,0xbbb6bbff,0xbb30bbdd,0xbbe2bbfa,0xbb02bbc9,0x3179acb5,0x37b73365,0xba4fbb50,0xb807b9ba,0x38ec367c,0x3ae93996,
0xaa4833c6,0xb1db304e,0xbbfebbc3,0xbbddbbed,0xb8c4b564,0xb9dcb7b7,0xba6dbb88,0xb972bb02,0xb95fbadd,0xb64eb94d,0x39ed381d,0x3b5a39fe,0xb0b2b6d7,0x3365ad7e,0x3bea3b3b,0x3bc93bf8,
0xb5052648,0xb705ad7e,0xbb99bbff,0xbb30bbf8,0xbac2b8ec,0xbb6eb9dc,0xb848ba4f,0xb5f1b972,0xacb5b67c,0x3414af0e,0x3bfa3b50,0x3bbc3bf4,0x389b3444,0x3ab538b0,0x3a8a3bb6,0x385d3a7c,
0x34003400,0x80008000,0x0,0x34003400,0x34003400,0x80008000,0x0,0x34003400,0x34003400,0x80008000,0x0,0x34003400,0x34003400,0x80008000,0x0,0x34003400,
0x33643400,0x2e1f8000,0xae1f0000,0x33643400,0x2e1f31a8,0x336431a8,0xb364b1a8,0x2e1f31a8,0xb364b400,0xae1f0000,0x2e1f8000,0xb364b400,0xae1fb1a8,0xb364b1a8,0x336431a8,0xae1fb1a8,
0x31a83400,0x31a88000,0xb1a80000,0x31a83400,0xb1a80000,0x31a83400,0xb1a8b400,0xb1a80000,0x31a83400,0x31a88000,0xb1a80000,0x31a83400,0xb1a80000,0x31a83400,0xb1a8b400,0xb1a80000,
0x2e1f3400,0x33648000,0xb3640000,0x2e1f3400,0xb364b1a8,0xae1f31a8,0x2e1fb1a8,0xb364b1a8,0xae1fb400,0xb3640000,0x33648000,0xae1fb400,0x336431a8,0x2e1fb1a8,0xae1f31a8,0x336431a8,
0x3400,0x34008000,0xb4000000,0x3400,0x8000b400,0xb4000000,0x34008000,0x8000b400,0x3400,0x34008000,0xb4000000,0x3400,0x8000b400,0xb4000000,0x34008000,0x8000b400,
0xae1f3400,0x33648000,0xb3640000,0xae1f3400,0x3364b1a8,0xae1fb1a8,0x2e1f31a8,0x3364b1a8,0x2e1fb400,0xb3640000,0x33648000,0x2e1fb400,0xb36431a8,0x2e1f31a8,0xae1fb1a8,0xb36431a8,
0xb1a83400,0x31a88000,0xb1a80000,0xb1a83400,0x31a88000,0x31a8b400,0xb1a83400,0x31a88000,0xb1a83400,0x31a88000,0xb1a80000,0xb1a83400,0x31a88000,0x31a8b400,0xb1a83400,0x31a88000,
0xb3643400,0x2e1f8000,0xae1f0000,0xb3643400,0xae1f31a8,0x3364b1a8,0xb36431a8,0xae1f31a8,0x3364b400,0xae1f0000,0x2e1f8000,0x3364b400,0x2e1fb1a8,0xb36431a8,0x3364b1a8,0x2e1fb1a8,
0xb4003400,0x8000,0x80000000,0xb4003400,0xb4003400,0x8000,0x80000000,0xb4003400,0xb4003400,0x8000,0x80000000,0xb4003400,0xb4003400,0x8000,0x80000000,0xb4003400,
0xb3643400,0xae1f8000,0x2e1f0000,0xb3643400,0xae1f31a8,0xb36431a8,0x3364b1a8,0xae1f31a8,0x3364b400,0x2e1f0000,0xae1f8000,0x3364b400,0x2e1fb1a8,0x3364b1a8,0xb36431a8,0x2e1fb1a8,
0xb1a83400,0xb1a88000,0x31a80000,0xb1a83400,0x31a80000,0xb1a83400,0x31a8b400,0x31a80000,0xb1a83400,0xb1a88000,0x31a80000,0xb1a83400,0x31a80000,0xb1a83400,0x31a8b400,0x31a80000,
0xae1f3400,0xb3648000,0x33640000,0xae1f3400,0x3364b1a8,0x2e1f31a8,0xae1fb1a8,0x3364b1a8,0x2e1fb400,0x33640000,0xb3648000,0x2e1fb400,0xb36431a8,0xae1fb1a8,0x2e1f31a8,0xb36431a8,
0x80003400,0xb4008000,0x34000000,0x80003400,0xb400,0x34000000,0xb4008000,0xb400,0x80003400,0xb4008000,0x34000000,0x80003400,0xb400,0x34000000,0xb4008000,0xb400,
0x2e1f3400,0xb3648000,0x33640000,0x2e1f3400,0xb364b1a8,0x2e1fb1a8,0xae1f31a8,0xb364b1a8,0xae1fb400,0x33640000,0xb3648000,0xae1fb400,0x336431a8,0xae1f31a8,0x2e1fb1a8,0x336431a8,
0x31a83400,0xb1a88000,0x31a80000,0x31a83400,0xb1a88000,0xb1a8b400,0x31a83400,0xb1a88000,0x31a83400,0xb1a88000,0x31a80000,0x31a83400,0xb1a88000,0xb1a8b400,0x31a83400,0xb1a88000,
0x33643400,0xae1f8000,0x2e1f0000,0x33643400,0x2e1f31a8,0xb364b1a8,0x336431a8,0x2e1f31a8,0xb364b400,0x2e1f0000,0xae1f8000,0xb364b400,0xae1fb1a8,0x336431a8,0xb364b1a8,0xae1fb1a8,
0x34003400,0x80008000,0x0,0x34003400,0x34003400,0x80008000,0x0,0x34003400,0x34003400,0x80008000,0x0,0x34003400,0x34003400,0x80008000,0x0,0x34003400,
0x32a733d9,0x30722a3e,0xb072aa3e,0x32a733d9,0x2a3e3072,0x33d932a7,0xb3d9b2a7,0x2a3e3072,0xb2a7b3d9,0xb072aa3e,0x30722a3e,0xb2a7b3d9,0xaa3eb072,0xb3d9b2a7,0x33d932a7,0xaa3eb072,
0x2e1f3364,0x33642e1f,0xb364ae1f,0x2e1f3364,0xb364ae1f,0x2e1f3364,0xae1fb364,0xb364ae1f,0x2e1f3364,0x33642e1f,0xb364ae1f,0x2e1f3364,0xb364ae1f,0x2e1f3364,0xae1fb364,0xb364ae1f,
0xaa3e32a7,0x33d93072,0xb3d9b072,0xaa3e32a7,0xb072b3d9,0xb2a72a3e,0x32a7aa3e,0xb072b3d9,0x2a3eb2a7,0xb3d9b072,0x33d93072,0x2a3eb2a7,0x307233d9,0x32a7aa3e,0xb2a72a3e,0x307233d9,
0xb1a831a8,0x31a831a8,0xb1a8b1a8,0xb1a831a8,0x31a8b1a8,0xb1a8b1a8,0x31a831a8,0x31a8b1a8,0xb1a831a8,0x31a831a8,0xb1a8b1a8,0xb1a831a8,0x31a8b1a8,0xb1a8b1a8,0x31a831a8,0x31a8b1a8,
0xb3d93072,0x2a3e32a7,0xaa3eb2a7,0xb3d93072,0x32a72a3e,0x3072b3d9,0xb07233d9,0x32a72a3e,0x33d9b072,0xaa3eb2a7,0x2a3e32a7,0x33d9b072,0xb2a7aa3e,0xb07233d9,0x3072b3d9,0xb2a7aa3e,
0xb3642e1f,0xae1f3364,0x2e1fb364,0xb3642e1f,0xae1f3364,0x3364ae1f,0xb3642e1f,0xae1f3364,0xb3642e1f,0xae1f3364,0x2e1fb364,0xb3642e1f,0xae1f3364,0x3364ae1f,0xb3642e1f,0xae1f3364,
0xb0722a3e,0xb2a733d9,0x32a7b3d9,0xb0722a3e,0xb3d932a7,0xaa3e3072,0x2a3eb072,0xb3d932a7,0x3072aa3e,0x32a7b3d9,0xb2a733d9,0x3072aa3e,0x33d9b2a7,0x2a3eb072,0xaa3e3072,0x33d9b2a7,
0x80000000,0xb4003400,0x3400b400,0x80000000,0x80000000,0xb4003400,0x3400b400,0x80000000,0x80000000,0xb4003400,0x3400b400,0x80000000,0x80000000,0xb4003400,0x3400b400,0x80000000,
0x3072aa3e,0xb2a733d9,0x32a7b3d9,0x3072aa3e,0x33d9b2a7,0xaa3e3072,0x2a3eb072,0x33d9b2a7,0xb0722a3e,0x32a7b3d9,0xb2a733d9,0xb0722a3e,0xb3d932a7,0x2a3eb072,0xaa3e3072,0xb3d932a7,
0x3364ae1f,0xae1f3364,0x2e1fb364,0x3364ae1f,0x2e1fb364,0x3364ae1f,0xb3642e1f,0x2e1fb364,0x3364ae1f,0xae1f3364,0x2e1fb364,0x3364ae1f,0x2e1fb364,0x3364ae1f,0xb3642e1f,0x2e1fb364,
0x33d9b072,0x2a3e32a7,0xaa3eb2a7,0x33d9b072,0xb2a7aa3e,0x3072b3d9,0xb07233d9,0xb2a7aa3e,0xb3d93072,0xaa3eb2a7,0x2a3e32a7,0xb3d93072,0x32a72a3e,0xb07233d9,0x3072b3d9,0x32a72a3e,
0x31a8b1a8,0x31a831a8,0xb1a8b1a8,0x31a8b1a8,0xb1a831a8,0xb1a8b1a8,0x31a831a8,0xb1a831a8,0x31a8b1a8,0x31a831a8,0xb1a8b1a8,0x31a8b1a8,0xb1a831a8,0xb1a8b1a8,0x31a831a8,0xb1a831a8,
0x2a3eb2a7,0x33d93072,0xb3d9b072,0x2a3eb2a7,0x307233d9,0xb2a72a3e,0x32a7aa3e,0x307233d9,0xaa3e32a7,0xb3d9b072,0x33d93072,0xaa3e32a7,0xb072b3d9,0x32a7aa3e,0xb2a72a3e,0xb072b3d9,
0xae1fb364,0x33642e1f,0xb364ae1f,0xae1fb364,0x33642e1f,0x2e1f3364,0xae1fb364,0x33642e1f,0xae1fb364,0x33642e1f,0xb364ae1f,0xae1fb364,0x33642e1f,0x2e1f3364,0xae1fb364,0x33642e1f,
0xb2a7b3d9,0x30722a3e,0xb072aa3e,0xb2a7b3d9,0xaa3eb072,0x33d932a7,0xb3d9b2a7,0xaa3eb072,0x32a733d9,0xb072aa3e,0x30722a3e,0x32a733d9,0x2a3e3072,0xb3d9b2a7,0x33d932a7,0x2a3e3072,
0x34003400,0x80008000,0x0,0x34003400,0x34003400,0x80008000,0x0,0x34003400,0x34003400,0x80008000,0x0,0x34003400,0x34003400,0x80008000,0x0,0x34003400,
0xae1f0000,0x33643400,0xb364b400,0xae1f0000,0xb364b1a8,0x2e1f31a8,0xae1fb1a8,0xb364b1a8,0x2e1f8000,0xb364b400,0x33643400,0x2e1f8000,0x336431a8,0xae1fb1a8,0x2e1f31a8,0x336431a8,
0xb1a8b400,0xb1a80000,0x31a88000,0xb1a8b400,0x31a88000,0xb1a8b400,0x31a83400,0x31a88000,0xb1a8b400,0xb1a80000,0x31a88000,0xb1a8b400,0x31a88000,0xb1a8b400,0x31a83400,0x31a88000,
0x33648000,0xae1fb400,0x2e1f3400,0x33648000,0xae1f31a8,0x336431a8,0xb364b1a8,0xae1f31a8,0xb3640000,0x2e1f3400,0xae1fb400,0xb3640000,0x2e1fb1a8,0xb364b1a8,0x336431a8,0x2e1fb1a8,
0x3400,0x34008000,0xb4000000,0x3400,0x8000b400,0xb4000000,0x34008000,0x8000b400,0x3400,0x34008000,0xb4000000,0x3400,0x8000b400,0xb4000000,0x34008000,0x8000b400,
0xb3640000,0xae1f3400,0x2e1fb400,0xb3640000,0x2e1f31a8,0x3364b1a8,0xb36431a8,0x2e1f31a8,0x33648000,0x2e1fb400,0xae1f3400,0x33648000,0xae1fb1a8,0xb36431a8,0x3364b1a8,0xae1fb1a8,
0x31a8b400,0xb1a80000,0x31a88000,0x31a8b400,0xb1a80000,0xb1a83400,0x31a8b400,0xb1a80000,0x31a8b400,0xb1a80000,0x31a88000,0x31a8b400,0xb1a80000,0xb1a83400,0x31a8b400,0xb1a80000,
0x2e1f8000,0x3364b400,0xb3643400,0x2e1f8000,0x3364b1a8,0x2e1fb1a8,0xae1f31a8,0x3364b1a8,0xae1f0000,0xb3643400,0x3364b400,0xae1f0000,0xb36431a8,0xae1f31a8,0x2e1fb1a8,0xb36431a8,
0xb4003400,0x8000,0x80000000,0xb4003400,0xb4003400,0x8000,0x80000000,0xb4003400,0xb4003400,0x8000,0x80000000,0xb4003400,0xb4003400,0x8000,0x80000000,0xb4003400,
0x2e1f0000,0xb3643400,0x3364b400,0x2e1f0000,0x3364b1a8,0xae1f31a8,0x2e1fb1a8,0x3364b1a8,0xae1f8000,0x3364b400,0xb3643400,0xae1f8000,0xb36431a8,0x2e1fb1a8,0xae1f31a8,0xb36431a8,
0x31a8b400,0x31a80000,0xb1a88000,0x31a8b400,0xb1a88000,0x31a8b400,0xb1a83400,0xb1a88000,0x31a8b400,0x31a80000,0xb1a88000,0x31a8b400,0xb1a88000,0x31a8b400,0xb1a83400,0xb1a88000,
0xb3648000,0x2e1fb400,0xae1f3400,0xb3648000,0x2e1f31a8,0xb36431a8,0x3364b1a8,0x2e1f31a8,0x33640000,0xae1f3400,0x2e1fb400,0x33640000,0xae1fb1a8,0x3364b1a8,0xb36431a8,0xae1fb1a8,
0x80003400,0xb4008000,0x34000000,0x80003400,0xb400,0x34000000,0xb4008000,0xb400,0x80003400,0xb4008000,0x34000000,0x80003400,0xb400,0x34000000,0xb4008000,0xb400,
0x33640000,0x2e1f3400,0xae1fb400,0x33640000,0xae1f31a8,0xb364b1a8,0x336431a8,0xae1f31a8,0xb3648000,0xae1fb400,0x2e1f3400,0xb3648000,0x2e1fb1a8,0x336431a8,0xb364b1a8,0x2e1fb1a8,
0xb1a8b400,0x31a80000,0xb1a88000,0xb1a8b400,0x31a80000,0x31a83400,0xb1a8b400,0x31a80000,0xb1a8b400,0x31a80000,0xb1a88000,0xb1a8b400,0x31a80000,0x31a83400,0xb1a8b400,0x31a80000,
0xae1f8000,0xb364b400,0x33643400,0xae1f8000,0xb364b1a8,0xae1fb1a8,0x2e1f31a8,0xb364b1a8,0x2e1f0000,0x33643400,0xb364b400,0x2e1f0000,0x336431a8,0x2e1f31a8,0xae1fb1a8,0x336431a8,
0x34003400,0x80008000,0x0,0x34003400,0x34003400,0x80008000,0x0,0x34003400,0x34003400,0x80008000,0x0,0x34003400,0x34003400,0x80008000,0x0,0x34003400,
0xb072aa3e,0x32a733d9,0xb2a7b3d9,0xb072aa3e,0xb3d9b2a7,0x2a3e3072,0xaa3eb072,0xb3d9b2a7,0x30722a3e,0xb2a7b3d9,0x32a733d9,0x30722a3e,0x33d932a7,0xaa3eb072,0x2a3e3072,0x33d932a7,
0xae1fb364,0xb364ae1f,0x33642e1f,0xae1fb364,0x33642e1f,0xae1fb364,0x2e1f3364,0x33642e1f,0xae1fb364,0xb364ae1f,0x33642e1f,0xae1fb364,0x33642e1f,0xae1fb364,0x2e1f3364,0x33642e1f,
0x33d93072,0x2a3eb2a7,0xaa3e32a7,0x33d93072,0xb2a72a3e,0x307233d9,0xb072b3d9,0xb2a72a3e,0xb3d9b072,0xaa3e32a7,0x2a3eb2a7,0xb3d9b072,0x32a7aa3e,0xb072b3d9,0x307233d9,0x32a7aa3e,
0xb1a831a8,0x31a831a8,0xb1a8b1a8,0xb1a831a8,0x31a8b1a8,0xb1a8b1a8,0x31a831a8,0x31a8b1a8,0xb1a831a8,0x31a831a8,0xb1a8b1a8,0xb1a831a8,0x31a8b1a8,0xb1a8b1a8,0x31a831a8,0x31a8b1a8,
0xaa3eb2a7,0xb3d93072,0x33d9b072,0xaa3eb2a7,0xb07233d9,0x32a72a3e,0xb2a7aa3e,0xb07233d9,0x2a3e32a7,0x33d9b072,0xb3d93072,0x2a3e32a7,0x3072b3d9,0xb2a7aa3e,0x32a72a3e,0x3072b3d9,
0x3364ae1f,0x2e1fb364,0xae1f3364,0x3364ae1f,0x2e1fb364,0xb3642e1f,0x3364ae1f,0x2e1fb364,0x3364ae1f,0x2e1fb364,0xae1f3364,0x3364ae1f,0x2e1fb364,0xb3642e1f,0x3364ae1f,0x2e1fb364,
0xb2a733d9,0x3072aa3e,0xb0722a3e,0xb2a733d9,0xaa3e3072,0x33d9b2a7,0xb3d932a7,0xaa3e3072,0x32a7b3d9,0xb0722a3e,0x3072aa3e,0x32a7b3d9,0x2a3eb072,0xb3d932a7,0x33d9b2a7,0x2a3eb072,
0x80000000,0xb4003400,0x3400b400,0x80000000,0x80000000,0xb4003400,0x3400b400,0x80000000,0x80000000,0xb4003400,0x3400b400,0x80000000,0x80000000,0xb4003400,0x3400b400,0x80000000,
0x32a7b3d9,0x3072aa3e,0xb0722a3e,0x32a7b3d9,0x2a3eb072,0x33d9b2a7,0xb3d932a7,0x2a3eb072,0xb2a733d9,0xb0722a3e,0x3072aa3e,0xb2a733d9,0xaa3e3072,0xb3d932a7,0x33d9b2a7,0xaa3e3072,
0xb3642e1f,0x2e1fb364,0xae1f3364,0xb3642e1f,0xae1f3364,0xb3642e1f,0x3364ae1f,0xae1f3364,0xb3642e1f,0x2e1fb364,0xae1f3364,0xb3642e1f,0xae1f3364,0xb3642e1f,0x3364ae1f,0xae1f3364,
0x2a3e32a7,0xb3d93072,0x33d9b072,0x2a3e32a7,0x3072b3d9,0x32a72a3e,0xb2a7aa3e,0x3072b3d9,0xaa3eb2a7,0x33d9b072,0xb3d93072,0xaa3eb2a7,0xb07233d9,0xb2a7aa3e,0x32a72a3e,0xb07233d9,
0x31a8b1a8,0x31a831a8,0xb1a8b1a8,0x31a8b1a8,0xb1a831a8,0xb1a8b1a8,0x31a831a8,0xb1a831a8,0x31a8b1a8,0x31a831a8,0xb1a8b1a8,0x31a8b1a8,0xb1a831a8,0xb1a8b1a8,0x31a831a8,0xb1a831a8,
0xb3d9b072,0x2a3eb2a7,0xaa3e32a7,0xb3d9b072,0x32a7aa3e,0x307233d9,0xb072b3d9,0x32a7aa3e,0x33d93072,0xaa3e32a7,0x2a3eb2a7,0x33d93072,0xb2a72a3e,0xb072b3d9,0x307233d9,0xb2a72a3e,
0x2e1f3364,0xb364ae1f,0x33642e1f,0x2e1f3364,0xb364ae1f,0xae1fb364,0x2e1f3364,0xb364ae1f,0x2e1f3364,0xb364ae1f,0x33642e1f,0x2e1f3364,0xb364ae1f,0xae1fb364,0x2e1f3364,0xb364ae1f,
0x30722a3e,0x32a733d9,0xb2a7b3d9,0x30722a3e,0x33d932a7,0x2a3e3072,0xaa3eb072,0x33d932a7,0xb072aa3e,0xb2a7b3d9,0x32a733d9,0xb072aa3e,0xb3d9b2a7,0xaa3eb072,0x2a3e3072,0xb3d9b2a7,
0x34003400,0x34003400,0xb4003400,0x80000000,0x34003400,0x34003400,0xb4003400,0x80000000,0x34003400,0x34003400,0xb4003400,0x80000000,0x34003400,0x34003400,0xb4003400,0x80000000,
0x3400,0xb1a831a8,0x80003400,0x31a8b1a8,0x8000b400,0x31a8b1a8,0xb400,0xb1a831a8,0x3400,0xb1a831a8,0x80003400,0x31a8b1a8,0x8000b400,0x31a8b1a8,0xb400,0xb1a831a8,
0x31a83400,0x2e1f3364,0xb1a83400,0x3364ae1f,0xb1a80000,0xb364ae1f,0x31a80000,0x2e1fb364,0xb1a8b400,0xae1fb364,0x31a8b400,0xb3642e1f,0x31a88000,0x33642e1f,0xb1a88000,0xae1f3364,
0xb1a83400,0xb3642e1f,0x31a83400,0xae1fb364,0x31a88000,0xae1f3364,0xb1a88000,0x33642e1f,0x31a8b400,0x3364ae1f,0xb1a8b400,0x2e1f3364,0xb1a80000,0x2e1fb364,0x31a80000,0xb364ae1f,
0x34003400,0xb400b400,0xb4003400,0x8000,0x34003400,0xb400b400,0xb4003400,0x8000,0x34003400,0xb400b400,0xb4003400,0x8000,0x34003400,0xb400b400,0xb4003400,0x8000,
0x3400,0x31a8b1a8,0x80003400,0xb1a831a8,0x8000b400,0xb1a831a8,0xb400,0x31a8b1a8,0x3400,0x31a8b1a8,0x80003400,0xb1a831a8,0x8000b400,0xb1a831a8,0xb400,0x31a8b1a8,
0x31a83400,0xae1fb364,0xb1a83400,0xb3642e1f,0xb1a80000,0x33642e1f,0x31a80000,0xae1f3364,0xb1a8b400,0x2e1f3364,0x31a8b400,0x3364ae1f,0x31a88000,0xb364ae1f,0xb1a88000,0x2e1fb364,
0xb1a83400,0x3364ae1f,0x31a83400,0x2e1f3364,0x31a88000,0x2e1fb364,0xb1a88000,0xb364ae1f,0x31a8b400,0xb3642e1f,0xb1a8b400,0xae1fb364,0xb1a80000,0xae1f3364,0x31a80000,0x33642e1f,
0x0,0x0,0x80000000,0x3400b400,0x0,0x0,0x80000000,0x3400b400,0x0,0x0,0x80000000,0x3400b400,0x0,0x0,0x80000000,0x3400b400,
0xb4000000,0xb1a8b1a8,0x34000000,0xb1a8b1a8,0x34008000,0x31a831a8,0xb4008000,0x31a831a8,0xb4000000,0xb1a8b1a8,0x34000000,0xb1a8b1a8,0x34008000,0x31a831a8,0xb4008000,0x31a831a8,
0xb1a80000,0xb364ae1f,0x31a80000,0x2e1fb364,0xb1a8b400,0xae1fb364,0x31a8b400,0xb3642e1f,0x31a88000,0x33642e1f,0xb1a88000,0xae1f3364,0x31a83400,0x2e1f3364,0xb1a83400,0x3364ae1f,
0xb1a80000,0x2e1fb364,0x31a80000,0xb364ae1f,0xb1a83400,0xb3642e1f,0x31a83400,0xae1fb364,0x31a88000,0xae1f3364,0xb1a88000,0x33642e1f,0x31a8b400,0x3364ae1f,0xb1a8b400,0x2e1f3364,
0x0,0x80008000,0x80000000,0xb4003400,0x0,0x80008000,0x80000000,0xb4003400,0x0,0x80008000,0x80000000,0xb4003400,0x0,0x80008000,0x80000000,0xb4003400,
0xb4000000,0x31a831a8,0x34000000,0x31a831a8,0x34008000,0xb1a8b1a8,0xb4008000,0xb1a8b1a8,0xb4000000,0x31a831a8,0x34000000,0x31a831a8,0x34008000,0xb1a8b1a8,0xb4008000,0xb1a8b1a8,
0xb1a80000,0x33642e1f,0x31a80000,0xae1f3364,0xb1a8b400,0x2e1f3364,0x31a8b400,0x3364ae1f,0x31a88000,0xb364ae1f,0xb1a88000,0x2e1fb364,0x31a83400,0xae1fb364,0xb1a83400,0xb3642e1f,
0xb1a80000,0xae1f3364,0x31a80000,0x33642e1f,0xb1a83400,0x3364ae1f,0x31a83400,0x2e1f3364,0x31a88000,0x2e1fb364,0xb1a88000,0xb364ae1f,0x31a8b400,0xb3642e1f,0xb1a8b400,0xae1fb364,
0x3c003c00,0x3c003c00,0x0,0x0,0x3c003c00,0x3c003c00,0x0,0x0,0x3c003c00,0x3c003c00,0x0,0x0,0x3c003c00,0x3c003c00,0x0,0x0,
0x3bfe3c00,0x3bfa3bff,0xaa480000,0xacb5a648,0x3bea3bf6,0x3be23bf1,0xb0b2ae46,0xb179afd6,0x3bc33bd9,0x3bb63bce,0xb3c6b23e,0xb444b303,0x3b883ba8,0x3b773b99,0xb564b4a5,0xb5c2b505,
0x3bf63c00,0x3bea3bfe,0xae460000,0xb0b2aa48,0x3ba83bd9,0x3b883bc3,0xb4a5b23e,0xb564b3c6,0x3b0e3b64,0x3add3b3b,0xb78bb61f,0xb81db6d7,0x3a2f3aa7,0x39ed3a6d,0xb913b872,0xb95fb8c4,
0x3bea3c00,0x3bce3bfa,0xb0b20000,0xb303acb5,0x3b3b3ba8,0x3af63b77,0xb6d7b4a5,0xb7e3b5c2,0x39ed3aa7,0x39843a4f,0xb95fb872,0xb9cbb8ec,0x381d3913,0x3732389b,0xbaddba2f,0xbb25ba8a,
0x3b643c00,0x3aa73bd9,0xb61f0000,0xb872b23e,0x361f39a8,0x323e3872,0xbb64b9a8,0xbbd9baa7,0xb61f0000,0xb872b23e,0xbb64bc00,0xbaa7bbd9,0xbb64b9a8,0xbbd9baa7,0xb61fb9a8,0xb23eb872,
0x3b3b3c00,0x3a4f3bce,0xb6d70000,0xb8ecb303,0x33c63913,0x26483732,0xbbc3ba2f,0xbbffbb25,0xb8c4b23e,0xba0fb67c,0xba6dbbd9,0xb93abb50,0xbbfebb0e,0xbbe2bbb6,0xaa48b78b,0x3179b444,
0x3b0e3c00,0x39ed3bc3,0xb78b0000,0xb95fb3c6,0x2e463872,0xb0b23564,0xbbf6baa7,0xbbeabb88,0xba2fb61f,0xbb3bb8c4,0xb913bb64,0xb6d7ba6d,0xbba8bbd9,0xbaddbbfe,0x34a5b23e,0x381d2a48,
0x3add3c00,0x39843bb6,0xb81d0000,0xb9cbb444,0xaa48378b,0xb5053303,0xbbfebb0e,0xbb99bbce,0xbb3bb872,0xbbe2ba0f,0xb6d7baa7,0xb179b93a,0xba6dbbf6,0xb8ecbb77,0x38c42e46,0x3a4f35c2,
0x3bff3c00,0x3bff3c00,0xa6480000,0xa8b6a248,0x3bfa3bfe,0x3bf83bfc,0xacb5aa48,0xad7eabd9,0x3bf13bf6,0x3bed3bf4,0xafd6ae46,0xb04eaf0e,0x3be23bea,0x3bdd3be6,0xb179b0b2,0xb1dbb115,
0x3bfa3c00,0x3bf43bff,0xacb50000,0xaf0ea8b6,0x3bce3bea,0x3bbc3bdd,0xb303b0b2,0xb414b1db,0x3b773ba8,0x3b5a3b91,0xb5c2b4a5,0xb64eb534,0x3af63b3b,0x3ad03b1a,0xb7e3b6d7,0xb832b75e,
0x3bf13c00,0x3bdd3bfc,0xafd60000,0xb1dbabd9,0x3b773bc3,0x3b463ba0,0xb5c2b3c6,0xb6aab4d5,0x3a8a3b0e,0x3a3f3ad0,0xb89bb78b,0xb900b832,0x393a39ed,0x38d83996,0xba0fb95f,0xba5eb9ba,
0x3be23c00,0x3bbc3bf8,0xb1790000,0xb414ad7e,0x3af63b88,0x3a993b46,0xb7e3b564,0xb887b6aa,0x393a3a2f,0x38b039ba,0xba0fb913,0xba7cb996,0x35c2381d,0x34753705,0xbb77badd,0xbbafbb30,
0x3b503c00,0x3a7c3bd4,0xb67c0000,0xb8b0b2a1,0x3505395f,0x2f0e3807,0xbb99b9ed,0xbbf4bae9,0xb7e3ae46,0xb94db4d5,0xbaf6bbf6,0xb9febba0,0xbbceba6d,0xbc00bb46,0xb303b8c4,0xa248b6aa,
0x3b253c00,0x3a1f3bc9,0xb7320000,0xb927b365,0x317938c4,0xabd9364e,0xbbe2ba6d,0xbbfcbb5a,0xb984b4a5,0xbab5b807,0xb9cbbba8,0xb85dbae9,0xbbf1bb88,0xbb80bbf4,0x2fd6b564,0x3593af0e,
0x3af63c00,0x39ba3bbc,0xb7e30000,0xb996b414,0x2648381d,0xb3653475,0xbbffbadd,0xbbc9bbaf,0xbac2b78b,0xbba0b972,0xb848bb0e,0xb4d5b9dc,0xbb25bbfe,0xb9febbd4,0x3732aa48,0x394d32a1,
0x3ac23c00,0x394d3baf,0xb8480000,0xb9feb475,0xafd636d7,0xb64e3115,0xbbf1bb3b,0xbb5abbe6,0xbb99b913,0xbbffba99,0xb505ba2f,0xa8b6b887,0xb984bbc3,0xb75ebae9,0x39cb33c6,0x3b1a3807,
0x3bd93c00,0x3ba83bf6,0xb23e0000,0xb4a5ae46,0x3aa73b64,0x3a2f3b0e,0xb872b61f,0xb913b78b,0x387239a8,0x378b3913,0xbaa7b9a8,0xbb0eba2f,0x323e361f,0x2e4634a5,0xbbd9bb64,0xbbf6bba8,
0x3bc33c00,0x3b773bf1,0xb3c60000,0xb5c2afd6,0x39ed3b0e,0x393a3a8a,0xb95fb78b,0xba0fb89b,0x35643872,0x33033732,0xbb88baa7,0xbbcebb25,0xb0b22e46,0xb444a648,0xbbeabbf6,0xbbb6bbff,
0x3ba83c00,0x3b3b3bea,0xb4a50000,0xb6d7b0b2,0x39133aa7,0x381d39ed,0xba2fb872,0xbaddb95f,0x2e46361f,0xaa4833c6,0xbbf6bb64,0xbbfebbc3,0xb78bb23e,0xb8c4b564,0xbb0ebbd9,0xba6dbb88,
0x3b883c00,0x3af63be2,0xb5640000,0xb7e3b179,0x381d3a2f,0x35c2393a,0xbaddb913,0xbb77ba0f,0xb0b2323e,0xb5052648,0xbbeabbd9,0xbb99bbff,0xb9edb78b,0xbac2b8ec,0xb95fbb0e,0xb848ba4f,
0x3aa73c00,0x39133ba8,0xb8720000,0xba2fb4a5,0xb23e361f,0xb78b2e46,0xbbd9bb64,0xbb0ebbf6,0xbbd9b9a8,0xbbf6bb0e,0xb23eb9a8,0x2e46b78b,0xb872bb64,0xb4a5ba2f,0x3aa7361f,0x3ba83913,
0x3a6d3c00,0x389b3b99,0xb8c40000,0xba8ab505,0xb56434a5,0xb8eca648,0xbb88bba8,0xba4fbbff,0xbbfebaa7,0xbb77bbb6,0x2a48b872,0x35c2b444,0xb3c6ba2f,0x2cb5b848,0x3bc33913,0x3bfa3ac2,
0x3a2f3c00,0x381d3b88,0xb9130000,0xbaddb564,0xb78b323e,0xb9edb0b2,0xbb0ebbd9,0xb95fbbea,0xbba8bb64,0xba6dbbfe,0x34a5b61f,0x38c4aa48,0x2e46b872,0x36d7b3c6,0x3bf63aa7,0x3b3b3bc3,
0x39ed3c00,0x37323b77,0xb95f0000,0xbb25b5c2,0xb8c42e46,0xbac2b444,0xba6dbbf6,0xb848bbb6,0xbaddbbd9,0xb8ecbbe2,0x381db23e,0x3a4f3179,0x36d7b4a5,0x39cb2cb5,0x3b3b3ba8,0x39843bfa,
0x3bce3c00,0x3b913bf4,0xb3030000,0xb534af0e,0x3a4f3b3b,0x39ba3ad0,0xb8ecb6d7,0xb996b832,0x37323913,0x3593385d,0xbb25ba2f,0xbb80bab5,0x264833c6,0xad7e304e,0xbbffbbc3,0xbbf8bbed,
0x3bb63c00,0x3b5a3bed,0xb4440000,0xb64eb04e,0x39843add,0x38b03a3f,0xb9cbb81d,0xba7cb900,0x3303378b,0x2d7e3593,0xbbcebb0e,0xbbf8bb80,0xb505aa48,0xb705b1db,0xbb99bbfe,0xbb30bbdd,
0x3b993c00,0x3b1a3be6,0xb5050000,0xb75eb115,0x389b3a6d,0x37053996,0xba8ab8c4,0xbb30b9ba,0xa64834a5,0xb1db304e,0xbbffbba8,0xbbddbbed,0xb8ecb564,0xb9dcb7b7,0xba4fbb88,0xb972bb02,
0x3b773c00,0x3ad03bdd,0xb5c20000,0xb832b1db,0x373239ed,0x347538d8,0xbb25b95f,0xbbafba5e,0xb4442e46,0xb705ad7e,0xbbb6bbf6,0xbb30bbf8,0xbac2b8c4,0xbb6eb9dc,0xb848ba6d,0xb5f1b972,
0x3a8a3c00,0x38d83ba0,0xb89b0000,0xba5eb4d5,0xb4443564,0xb85d28b6,0xbbb6bb88,0xbab5bbff,0xbbfaba2f,0xbbc9bb6e,0xacb5b913,0x3365b5f1,0xb67cbadd,0xaf0eb94d,0x3b50381d,0x3bf439fe,
0x3a4f3c00,0x385d3b91,0xb8ec0000,0xbab5b534,0xb67c33c6,0xb972ad7e,0xbb50bbc3,0xb9dcbbf8,0xbbe2bb0e,0xbb02bbe6,0x3179b78b,0x37b7b115,0xacb5b95f,0x3414b64e,0x3bfa39ed,0x3bbc3b5a,
0x3a0f3c00,0x37b73b80,0xb93a0000,0xbb02b593,0xb84830b2,0xba5eb2a1,0xbac2bbea,0xb8d8bbd4,0xbb50bba8,0xb9babbfc,0x367cb4a5,0x39962bd9,0x3444b6d7,0x38b0ad7e,0x3bb63b3b,0x3a7c3bf8,
0x39cb3c00,0x36aa3b6e,0xb9840000,0xbb46b5f1,0xb93a2a48,0xbb1ab534,0xba0fbbfe,0xb75ebb91,0xba4fbbf6,0xb807bbaf,0x38ecae46,0x3ae93475,0x389bb0b2,0x3ab53365,0x3a8a3bea,0x385d3bc9,
0x34003400,0x80008000,0x0,0x34003400,0x34003400,0x80008000,0x0,0x34003400,0x34003400,0x80008000,0x0,0x34003400,0x34003400,0x80008000,0x0,0x34003400,
0x33643400,0x2e1f8000,0xae1f0000,0x33643400,0x2e1f31a8,0x336431a8,0xb364b1a8,0x2e1f31a8,0xae1f0000,0x33643400,0xb364b400,0xae1f0000,0xb364b1a8,0x2e1f31a8,0xae1fb1a8,0xb364b1a8,
0x31a83400,0x31a88000,0xb1a80000,0x31a83400,0xb1a80000,0x31a83400,0xb1a8b400,0xb1a80000,0xb1a8b400,0xb1a80000,0x31a88000,0xb1a8b400,0x31a88000,0xb1a8b400,0x31a83400,0x31a88000,
0x2e1f3400,0x33648000,0xb3640000,0x2e1f3400,0xb364b1a8,0xae1f31a8,0x2e1fb1a8,0xb364b1a8,0x33648000,0xae1fb400,0x2e1f3400,0x33648000,0xae1f31a8,0x336431a8,0xb364b1a8,0xae1f31a8,
0xb4003400,0x8000,0x80000000,0xb4003400,0xb4003400,0x8000,0x80000000,0xb4003400,0xb4003400,0x8000,0x80000000,0xb4003400,0xb4003400,0x8000,0x80000000,0xb4003400,
0xb3643400,0xae1f8000,0x2e1f0000,0xb3643400,0xae1f31a8,0xb36431a8,0x3364b1a8,0xae1f31a8,0x2e1f0000,0xb3643400,0x3364b400,0x2e1f0000,0x3364b1a8,0xae1f31a8,0x2e1fb1a8,0x3364b1a8,
0xb1a83400,0xb1a88000,0x31a80000,0xb1a83400,0x31a80000,0xb1a83400,0x31a8b400,0x31a80000,0x31a8b400,0x31a80000,0xb1a88000,0x31a8b400,0xb1a88000,0x31a8b400,0xb1a83400,0xb1a88000,
0xae1f3400,0xb3648000,0x33640000,0xae1f3400,0x3364b1a8,0x2e1f31a8,0xae1fb1a8,0x3364b1a8,0xb3648000,0x2e1fb400,0xae1f3400,0xb3648000,0x2e1f31a8,0xb36431a8,0x3364b1a8,0x2e1f31a8,
0x34003400,0x80008000,0x0,0x34003400,0x34003400,0x80008000,0x0,0x34003400,0x34003400,0x80008000,0x0,0x34003400,0x34003400,0x80008000,0x0,0x34003400,
0xb364b400,0xae1f0000,0x2e1f8000,0xb364b400,0xae1fb1a8,0xb364b1a8,0x336431a8,0xae1fb1a8,0x2e1f8000,0xb364b400,0x33643400,0x2e1f8000,0x336431a8,0xae1fb1a8,0x2e1f31a8,0x336431a8,
0x31a83400,0x31a88000,0xb1a80000,0x31a83400,0xb1a80000,0x31a83400,0xb1a8b400,0xb1a80000,0xb1a8b400,0xb1a80000,0x31a88000,0xb1a8b400,0x31a88000,0xb1a8b400,0x31a83400,0x31a88000,
0xae1fb400,0xb3640000,0x33648000,0xae1fb400,0x336431a8,0x2e1fb1a8,0xae1f31a8,0x336431a8,0xb3640000,0x2e1f3400,0xae1fb400,0xb3640000,0x2e1fb1a8,0xb364b1a8,0x336431a8,0x2e1fb1a8,
0xb4003400,0x8000,0x80000000,0xb4003400,0xb4003400,0x8000,0x80000000,0xb4003400,0xb4003400,0x8000,0x80000000,0xb4003400,0xb4003400,0x8000,0x80000000,0xb4003400,
0x3364b400,0x2e1f0000,0xae1f8000,0x3364b400,0x2e1fb1a8,0x3364b1a8,0xb36431a8,0x2e1fb1a8,0xae1f8000,0x3364b400,0xb3643400,0xae1f8000,0xb36431a8,0x2e1fb1a8,0xae1f31a8,0xb36431a8,
0xb1a83400,0xb1a88000,0x31a80000,0xb1a83400,0x31a80000,0xb1a83400,0x31a8b400,0x31a80000,0x31a8b400,0x31a80000,0xb1a88000,0x31a8b400,0xb1a88000,0x31a8b400,0xb1a83400,0xb1a88000,
0x2e1fb400,0x33640000,0xb3648000,0x2e1fb400,0xb36431a8,0xae1fb1a8,0x2e1f31a8,0xb36431a8,0x33640000,0xae1f3400,0x2e1fb400,0x33640000,0xae1fb1a8,0x3364b1a8,0xb36431a8,0xae1fb1a8,
0x33d93400,0x2a3e8000,0xaa3e0000,0x33d93400,0x32a73364,0x30722e1f,0xb072ae1f,0x32a73364,0x307231a8,0x32a731a8,0xb2a7b1a8,0x307231a8,0x2a3e2e1f,0x33d93364,0xb3d9b364,0x2a3e2e1f,
0x32a73400,0x30728000,0xb0720000,0x32a73400,0xaa3e2e1f,0x33d93364,0xb3d9b364,0xaa3e2e1f,0xb3d9b1a8,0x2a3e31a8,0xaa3eb1a8,0xb3d9b1a8,0xb072b364,0xb2a7ae1f,0x32a72e1f,0xb072b364,
0x30723400,0x32a78000,0xb2a70000,0x30723400,0xb3d9ae1f,0x2a3e3364,0xaa3eb364,0xb3d9ae1f,0x2a3eb1a8,0xb3d9b1a8,0x33d931a8,0x2a3eb1a8,0x32a73364,0x3072ae1f,0xb0722e1f,0x32a73364,
0x2a3e3400,0x33d98000,0xb3d90000,0x2a3e3400,0xb072b364,0xb2a72e1f,0x32a7ae1f,0xb072b364,0x32a731a8,0x3072b1a8,0xb07231a8,0x32a731a8,0xb3d9ae1f,0xaa3e3364,0x2a3eb364,0xb3d9ae1f,
0xb3d93400,0xaa3e8000,0x2a3e0000,0xb3d93400,0xb2a73364,0xb0722e1f,0x3072ae1f,0xb2a73364,0xb07231a8,0xb2a731a8,0x32a7b1a8,0xb07231a8,0xaa3e2e1f,0xb3d93364,0x33d9b364,0xaa3e2e1f,
0xb2a73400,0xb0728000,0x30720000,0xb2a73400,0x2a3e2e1f,0xb3d93364,0x33d9b364,0x2a3e2e1f,0x33d9b1a8,0xaa3e31a8,0x2a3eb1a8,0x33d9b1a8,0x3072b364,0x32a7ae1f,0xb2a72e1f,0x3072b364,
0xb0723400,0xb2a78000,0x32a70000,0xb0723400,0x33d9ae1f,0xaa3e3364,0x2a3eb364,0x33d9ae1f,0xaa3eb1a8,0x33d9b1a8,0xb3d931a8,0xaa3eb1a8,0xb2a73364,0xb072ae1f,0x30722e1f,0xb2a73364,
0xaa3e3400,0xb3d98000,0x33d90000,0xaa3e3400,0x3072b364,0x32a72e1f,0xb2a7ae1f,0x3072b364,0xb2a731a8,0xb072b1a8,0x307231a8,0xb2a731a8,0x33d9ae1f,0x2a3e3364,0xaa3eb364,0x33d9ae1f,
0xaa3e0000,0x33d93400,0xb3d9b400,0xaa3e0000,0xb072ae1f,0x32a73364,0xb2a7b364,0xb072ae1f,0xb2a7b1a8,0x307231a8,0xb072b1a8,0xb2a7b1a8,0xb3d9b364,0x2a3e2e1f,0xaa3eae1f,0xb3d9b364,
0x30728000,0xb2a7b400,0x32a73400,0x30728000,0x33d93364,0x2a3eae1f,0xaa3e2e1f,0x33d93364,0x2a3e31a8,0x33d931a8,0xb3d9b1a8,0x2a3e31a8,0xb2a7ae1f,0x30723364,0xb072b364,0xb2a7ae1f,
0xb2a70000,0x30723400,0xb072b400,0xb2a70000,0xaa3eb364,0xb3d9ae1f,0x33d92e1f,0xaa3eb364,0x33d931a8,0x2a3eb1a8,0xaa3e31a8,0x33d931a8,0xb0722e1f,0x32a73364,0xb2a7b364,0xb0722e1f,
0x33d98000,0xaa3eb400,0x2a3e3400,0x33d98000,0xb2a72e1f,0x30723364,0xb072b364,0xb2a72e1f,0x3072b1a8,0xb2a7b1a8,0x32a731a8,0x3072b1a8,0xaa3e3364,0x33d92e1f,0xb3d9ae1f,0xaa3e3364,
0x2a3e0000,0xb3d93400,0x33d9b400,0x2a3e0000,0x3072ae1f,0xb2a73364,0x32a7b364,0x3072ae1f,0x32a7b1a8,0xb07231a8,0x3072b1a8,0x32a7b1a8,0x33d9b364,0xaa3e2e1f,0x2a3eae1f,0x33d9b364,
0xb0728000,0x32a7b400,0xb2a73400,0xb0728000,0xb3d93364,0xaa3eae1f,0x2a3e2e1f,0xb3d93364,0xaa3e31a8,0xb3d931a8,0x33d9b1a8,0xaa3e31a8,0x32a7ae1f,0xb0723364,0x3072b364,0x32a7ae1f,
0x32a70000,0xb0723400,0x3072b400,0x32a70000,0x2a3eb364,0x33d9ae1f,0xb3d92e1f,0x2a3eb364,0xb3d931a8,0xaa3eb1a8,0x2a3e31a8,0xb3d931a8,0x30722e1f,0xb2a73364,0x32a7b364,0x30722e1f,
0xb3d98000,0x2a3eb400,0xaa3e3400,0xb3d98000,0x32a72e1f,0xb0723364,0x3072b364,0x32a72e1f,0xb072b1a8,0x32a7b1a8,0xb2a731a8,0xb072b1a8,0x2a3e3364,0xb3d92e1f,0x33d9ae1f,0x2a3e3364,
0x3400,0x34008000,0xb4000000,0x3400,0x8000b400,0xb4000000,0x34008000,0x8000b400,0x3400,0x34008000,0xb4000000,0x3400,0x8000b400,0xb4000000,0x34008000,0x8000b400,
0xae1f3400,0x33648000,0xb3640000,0xae1f3400,0x3364b1a8,0xae1fb1a8,0x2e1f31a8,0x3364b1a8,0xb3640000,0xae1f3400,0x2e1fb400,0xb3640000,0x2e1f31a8,0x3364b1a8,0xb36431a8,0x2e1f31a8,
0xb1a83400,0x31a88000,0xb1a80000,0xb1a83400,0x31a88000,0x31a8b400,0xb1a83400,0x31a88000,0x31a8b400,0xb1a80000,0x31a88000,0x31a8b400,0xb1a80000,0xb1a83400,0x31a8b400,0xb1a80000,
0xb3643400,0x2e1f8000,0xae1f0000,0xb3643400,0xae1f31a8,0x3364b1a8,0xb36431a8,0xae1f31a8,0x2e1f8000,0x3364b400,0xb3643400,0x2e1f8000,0x3364b1a8,0x2e1fb1a8,0xae1f31a8,0x3364b1a8,
0x80003400,0xb4008000,0x34000000,0x80003400,0xb400,0x34000000,0xb4008000,0xb400,0x80003400,0xb4008000,0x34000000,0x80003400,0xb400,0x34000000,0xb4008000,0xb400,
0x2e1f3400,0xb3648000,0x33640000,0x2e1f3400,0xb364b1a8,0x2e1fb1a8,0xae1f31a8,0xb364b1a8,0x33640000,0x2e1f3400,0xae1fb400,0x33640000,0xae1f31a8,0xb364b1a8,0x336431a8,0xae1f31a8,
0x31a83400,0xb1a88000,0x31a80000,0x31a83400,0xb1a88000,0xb1a8b400,0x31a83400,0xb1a88000,0xb1a8b400,0x31a80000,0xb1a88000,0xb1a8b400,0x31a80000,0x31a83400,0xb1a8b400,0x31a80000,
0x33643400,0xae1f8000,0x2e1f0000,0x33643400,0x2e1f31a8,0xb364b1a8,0x336431a8,0x2e1f31a8,0xae1f8000,0xb364b400,0x33643400,0xae1f8000,0xb364b1a8,0xae1fb1a8,0x2e1f31a8,0xb364b1a8,
0x3400,0x34008000,0xb4000000,0x3400,0x8000b400,0xb4000000,0x34008000,0x8000b400,0x3400,0x34008000,0xb4000000,0x3400,0x8000b400,0xb4000000,0x34008000,0x8000b400,
0x2e1fb400,0xb3640000,0x33648000,0x2e1fb400,0xb36431a8,0x2e1f31a8,0xae1fb1a8,0xb36431a8,0x33648000,0x2e1fb400,0xae1f3400,0x33648000,0xae1fb1a8,0xb36431a8,0x3364b1a8,0xae1fb1a8,
0xb1a83400,0x31a88000,0xb1a80000,0xb1a83400,0x31a88000,0x31a8b400,0xb1a83400,0x31a88000,0x31a8b400,0xb1a80000,0x31a88000,0x31a8b400,0xb1a80000,0xb1a83400,0x31a8b400,0xb1a80000,
0x3364b400,0xae1f0000,0x2e1f8000,0x3364b400,0x2e1fb1a8,0xb36431a8,0x3364b1a8,0x2e1fb1a8,0xae1f0000,0xb3643400,0x3364b400,0xae1f0000,0xb36431a8,0xae1f31a8,0x2e1fb1a8,0xb36431a8,
0x80003400,0xb4008000,0x34000000,0x80003400,0xb400,0x34000000,0xb4008000,0xb400,0x80003400,0xb4008000,0x34000000,0x80003400,0xb400,0x34000000,0xb4008000,0xb400,
0xae1fb400,0x33640000,0xb3648000,0xae1fb400,0x336431a8,0xae1f31a8,0x2e1fb1a8,0x336431a8,0xb3648000,0xae1fb400,0x2e1f3400,0xb3648000,0x2e1fb1a8,0x336431a8,0xb364b1a8,0x2e1fb1a8,
0x31a83400,0xb1a88000,0x31a80000,0x31a83400,0xb1a88000,0xb1a8b400,0x31a83400,0xb1a88000,0xb1a8b400,0x31a80000,0xb1a88000,0xb1a8b400,0x31a80000,0x31a83400,0xb1a8b400,0x31a80000,
0xb364b400,0x2e1f0000,0xae1f8000,0xb364b400,0xae1fb1a8,0x336431a8,0xb364b1a8,0xae1fb1a8,0x2e1f0000,0x33643400,0xb364b400,0x2e1f0000,0x336431a8,0x2e1f31a8,0xae1fb1a8,0x336431a8,
0xaa3e3400,0x33d98000,0xb3d90000,0xaa3e3400,0x3072b364,0xb2a7ae1f,0x32a72e1f,0x3072b364,0xb2a731a8,0x307231a8,0xb072b1a8,0xb2a731a8,0x33d9ae1f,0xaa3eb364,0x2a3e3364,0x33d9ae1f,
0xb0723400,0x32a78000,0xb2a70000,0xb0723400,0x33d9ae1f,0x2a3eb364,0xaa3e3364,0x33d9ae1f,0xaa3eb1a8,0xb3d931a8,0x33d9b1a8,0xaa3eb1a8,0xb2a73364,0x30722e1f,0xb072ae1f,0xb2a73364,
0xb2a73400,0x30728000,0xb0720000,0xb2a73400,0x2a3e2e1f,0x33d9b364,0xb3d93364,0x2a3e2e1f,0x33d9b1a8,0x2a3eb1a8,0xaa3e31a8,0x33d9b1a8,0x3072b364,0xb2a72e1f,0x32a7ae1f,0x3072b364,
0xb3d93400,0x2a3e8000,0xaa3e0000,0xb3d93400,0xb2a73364,0x3072ae1f,0xb0722e1f,0xb2a73364,0xb07231a8,0x32a7b1a8,0xb2a731a8,0xb07231a8,0xaa3e2e1f,0x33d9b364,0xb3d93364,0xaa3e2e1f,
0x2a3e3400,0xb3d98000,0x33d90000,0x2a3e3400,0xb072b364,0x32a7ae1f,0xb2a72e1f,0xb072b364,0x32a731a8,0xb07231a8,0x3072b1a8,0x32a731a8,0xb3d9ae1f,0x2a3eb364,0xaa3e3364,0xb3d9ae1f,
0x30723400,0xb2a78000,0x32a70000,0x30723400,0xb3d9ae1f,0xaa3eb364,0x2a3e3364,0xb3d9ae1f,0x2a3eb1a8,0x33d931a8,0xb3d9b1a8,0x2a3eb1a8,0x32a73364,0xb0722e1f,0x3072ae1f,0x32a73364,
0x32a73400,0xb0728000,0x30720000,0x32a73400,0xaa3e2e1f,0xb3d9b364,0x33d93364,0xaa3e2e1f,0xb3d9b1a8,0xaa3eb1a8,0x2a3e31a8,0xb3d9b1a8,0xb072b364,0x32a72e1f,0xb2a7ae1f,0xb072b364,
0x33d93400,0xaa3e8000,0x2a3e0000,0x33d93400,0x32a73364,0xb072ae1f,0x30722e1f,0x32a73364,0x307231a8,0xb2a7b1a8,0x32a731a8,0x307231a8,0x2a3e2e1f,0xb3d9b364,0x33d93364,0x2a3e2e1f,
0xb3d90000,0xaa3e3400,0x2a3eb400,0xb3d90000,0x32a72e1f,0x3072b364,0xb0723364,0x32a72e1f,0xb072b1a8,0xb2a731a8,0x32a7b1a8,0xb072b1a8,0x2a3e3364,0x33d9ae1f,0xb3d92e1f,0x2a3e3364,
0x32a78000,0x3072b400,0xb0723400,0x32a78000,0x2a3eb364,0xb3d92e1f,0x33d9ae1f,0x2a3eb364,0xb3d931a8,0x2a3e31a8,0xaa3eb1a8,0xb3d931a8,0x30722e1f,0x32a7b364,0xb2a73364,0x30722e1f,
0xb0720000,0xb2a73400,0x32a7b400,0xb0720000,0xb3d93364,0x2a3e2e1f,0xaa3eae1f,0xb3d93364,0xaa3e31a8,0x33d9b1a8,0xb3d931a8,0xaa3e31a8,0x32a7ae1f,0x3072b364,0xb0723364,0x32a7ae1f,
0x2a3e8000,0x33d9b400,0xb3d93400,0x2a3e8000,0x3072ae1f,0x32a7b364,0xb2a73364,0x3072ae1f,0x32a7b1a8,0x3072b1a8,0xb07231a8,0x32a7b1a8,0x33d9b364,0x2a3eae1f,0xaa3e2e1f,0x33d9b364,
0x33d90000,0x2a3e3400,0xaa3eb400,0x33d90000,0xb2a72e1f,0xb072b364,0x30723364,0xb2a72e1f,0x3072b1a8,0x32a731a8,0xb2a7b1a8,0x3072b1a8,0xaa3e3364,0xb3d9ae1f,0x33d92e1f,0xaa3e3364,
0xb2a78000,0xb072b400,0x30723400,0xb2a78000,0xaa3eb364,0x33d92e1f,0xb3d9ae1f,0xaa3eb364,0x33d931a8,0xaa3e31a8,0x2a3eb1a8,0x33d931a8,0xb0722e1f,0xb2a7b364,0x32a73364,0xb0722e1f,
0x30720000,0x32a73400,0xb2a7b400,0x30720000,0x33d93364,0xaa3e2e1f,0x2a3eae1f,0x33d93364,0x2a3e31a8,0xb3d9b1a8,0x33d931a8,0x2a3e31a8,0xb2a7ae1f,0xb072b364,0x30723364,0xb2a7ae1f,
0xaa3e8000,0xb3d9b400,0x33d93400,0xaa3e8000,0xb072ae1f,0xb2a7b364,0x32a73364,0xb072ae1f,0xb2a7b1a8,0xb072b1a8,0x307231a8,0xb2a7b1a8,0xb3d9b364,0xaa3eae1f,0x2a3e2e1f,0xb3d9b364,
0x3c003c00,0x3b643c00,0x0,0xb61f0000,0x3c003c00,0x361f39a8,0x0,0xbb64b9a8,0x3c003c00,0xb61f0000,0x0,0xbb64bc00,0x3c003c00,0xbb64b9a8,0x0,0xb61fb9a8,
0x3bfe3c00,0x3b3b3c00,0xaa480000,0xb6d70000,0x3bea3bf6,0x33c63913,0xb0b2ae46,0xbbc3ba2f,0x3bc33bd9,0xb8c4b23e,0xb3c6b23e,0xba6dbbd9,0x3b883ba8,0xbbfebb0e,0xb564b4a5,0xaa48b78b,
0x3bf63c00,0x3b0e3c00,0xae460000,0xb78b0000,0x3ba83bd9,0x2e463872,0xb4a5b23e,0xbbf6baa7,0x3b0e3b64,0xba2fb61f,0xb78bb61f,0xb913bb64,0x3a2f3aa7,0xbba8bbd9,0xb913b872,0x34a5b23e,
0x3bea3c00,0x3add3c00,0xb0b20000,0xb81d0000,0x3b3b3ba8,0xaa48378b,0xb6d7b4a5,0xbbfebb0e,0x39ed3aa7,0xbb3bb872,0xb95fb872,0xb6d7baa7,0x381d3913,0xba6dbbf6,0xbaddba2f,0x38c42e46,
0x3bd93c00,0x3aa73c00,0xb23e0000,0xb8720000,0x3aa73b64,0xb23e361f,0xb872b61f,0xbbd9bb64,0x387239a8,0xbbd9b9a8,0xbaa7b9a8,0xb23eb9a8,0x323e361f,0xb872bb64,0xbbd9bb64,0x3aa7361f,
0x3bc33c00,0x3a6d3c00,0xb3c60000,0xb8c40000,0x39ed3b0e,0xb56434a5,0xb95fb78b,0xbb88bba8,0x35643872,0xbbfebaa7,0xbb88baa7,0x2a48b872,0xb0b22e46,0xb3c6ba2f,0xbbeabbf6,0x3bc33913,
0x3ba83c00,0x3a2f3c00,0xb4a50000,0xb9130000,0x39133aa7,0xb78b323e,0xba2fb872,0xbb0ebbd9,0x2e46361f,0xbba8bb64,0xbbf6bb64,0x34a5b61f,0xb78bb23e,0x2e46b872,0xbb0ebbd9,0x3bf63aa7,
0x3b883c00,0x39ed3c00,0xb5640000,0xb95f0000,0x381d3a2f,0xb8c42e46,0xbaddb913,0xba6dbbf6,0xb0b2323e,0xbaddbbd9,0xbbeabbd9,0x381db23e,0xb9edb78b,0x36d7b4a5,0xb95fbb0e,0x3b3b3ba8,
0x3c003c00,0x3c003c00,0x0,0x0,0x3c003c00,0x3c003c00,0x0,0x0,0x3c003c00,0x3c003c00,0x0,0x0,0x3c003c00,0x3c003c00,0x0,0x0,
0x3bfe3c00,0x3b3b3b64,0xaa480000,0xb6d7b61f,0x3bea3bf6,0x3add3b0e,0xb0b2ae46,0xb81db78b,0x3bc33bd9,0x3a6d3aa7,0xb3c6b23e,0xb8c4b872,0x3b883ba8,0x39ed3a2f,0xb564b4a5,0xb95fb913,
0x3bf63c00,0x391339a8,0xae460000,0xba2fb9a8,0x3ba83bd9,0x378b3872,0xb4a5b23e,0xbb0ebaa7,0x3b0e3b64,0x34a5361f,0xb78bb61f,0xbba8bb64,0x3a2f3aa7,0x2e46323e,0xb913b872,0xbbf6bbd9,
0x3bea3c00,0x33c6361f,0xb0b20000,0xbbc3bb64,0x3b3b3ba8,0xaa482e46,0xb6d7b4a5,0xbbfebbf6,0x39ed3aa7,0xb564b23e,0xb95fb872,0xbb88bbd9,0x381d3913,0xb8c4b78b,0xbaddba2f,0xba6dbb0e,
0x3bd93c00,0xb23e0000,0xb23e0000,0xbbd9bc00,0x3aa73b64,0xb872b61f,0xb872b61f,0xbaa7bb64,0x387239a8,0xbaa7b9a8,0xbaa7b9a8,0xb872b9a8,0x323e361f,0xbbd9bb64,0xbbd9bb64,0xb23eb61f,
0x3bc33c00,0xb8c4b61f,0xb3c60000,0xba6dbb64,0x39ed3b0e,0xbb3bba2f,0xb95fb78b,0xb6d7b913,0x35643872,0xbbfebbd9,0xbb88baa7,0x2a48b23e,0xb0b22e46,0xbaddbba8,0xbbeabbf6,0x381d34a5,
0x3ba83c00,0xbb0eb9a8,0xb4a50000,0xb78bb9a8,0x39133aa7,0xbbf6bbd9,0xba2fb872,0x2e46b23e,0x2e46361f,0xba2fbb64,0xbbf6bb64,0x3913361f,0xb78bb23e,0xb4a5b872,0xbb0ebbd9,0x3ba83aa7,
0x3b883c00,0xbbfebb64,0xb5640000,0xaa48b61f,0x381d3a2f,0xba6dbba8,0xbaddb913,0x38c434a5,0xb0b2323e,0xb3c6b872,0xbbeabbd9,0x3bc33aa7,0xb9edb78b,0x36d72e46,0xb95fbb0e,0x3b3b3bf6,
0x34003400,0x80008000,0x0,0x34003400,0x34003400,0x80008000,0x0,0x34003400,0x34003400,0x80008000,0x0,0x34003400,0x34003400,0x80008000,0x0,0x34003400,
0x33643400,0x2e1f8000,0xae1f0000,0x33643400,0x2e1f31a8,0x336431a8,0xb364b1a8,0x2e1f31a8,0xae1f0000,0x33643400,0xb364b400,0xae1f0000,0xb364b1a8,0x2e1f31a8,0xae1fb1a8,0xb364b1a8,
0x31a83400,0x31a88000,0xb1a80000,0x31a83400,0xb1a80000,0x31a83400,0xb1a8b400,0xb1a80000,0xb1a8b400,0xb1a80000,0x31a88000,0xb1a8b400,0x31a88000,0xb1a8b400,0x31a83400,0x31a88000,
0x2e1f3400,0x33648000,0xb3640000,0x2e1f3400,0xb364b1a8,0xae1f31a8,0x2e1fb1a8,0xb364b1a8,0x33648000,0xae1fb400,0x2e1f3400,0x33648000,0xae1f31a8,0x336431a8,0xb364b1a8,0xae1f31a8,
0x3400,0x34008000,0xb4000000,0x3400,0x8000b400,0xb4000000,0x34008000,0x8000b400,0x3400,0x34008000,0xb4000000,0x3400,0x8000b400,0xb4000000,0x34008000,0x8000b400,
0xae1f3400,0x33648000,0xb3640000,0xae1f3400,0x3364b1a8,0xae1fb1a8,0x2e1f31a8,0x3364b1a8,0xb3640000,0xae1f3400,0x2e1fb400,0xb3640000,0x2e1f31a8,0x3364b1a8,0xb36431a8,0x2e1f31a8,
0xb1a83400,0x31a88000,0xb1a80000,0xb1a83400,0x31a88000,0x31a8b400,0xb1a83400,0x31a88000,0x31a8b400,0xb1a80000,0x31a88000,0x31a8b400,0xb1a80000,0xb1a83400,0x31a8b400,0xb1a80000,
0xb3643400,0x2e1f8000,0xae1f0000,0xb3643400,0xae1f31a8,0x3364b1a8,0xb36431a8,0xae1f31a8,0x2e1f8000,0x3364b400,0xb3643400,0x2e1f8000,0x3364b1a8,0x2e1fb1a8,0xae1f31a8,0x3364b1a8,
0xb4003400,0x8000,0x80000000,0xb4003400,0xb4003400,0x8000,0x80000000,0xb4003400,0xb4003400,0x8000,0x80000000,0xb4003400,0xb4003400,0x8000,0x80000000,0xb4003400,
0xb3643400,0xae1f8000,0x2e1f0000,0xb3643400,0xae1f31a8,0xb36431a8,0x3364b1a8,0xae1f31a8,0x2e1f0000,0xb3643400,0x3364b400,0x2e1f0000,0x3364b1a8,0xae1f31a8,0x2e1fb1a8,0x3364b1a8,
0xb1a83400,0xb1a88000,0x31a80000,0xb1a83400,0x31a80000,0xb1a83400,0x31a8b400,0x31a80000,0x31a8b400,0x31a80000,0xb1a88000,0x31a8b400,0xb1a88000,0x31a8b400,0xb1a83400,0xb1a88000,
0xae1f3400,0xb3648000,0x33640000,0xae1f3400,0x3364b1a8,0x2e1f31a8,0xae1fb1a8,0x3364b1a8,0xb3648000,0x2e1fb400,0xae1f3400,0xb3648000,0x2e1f31a8,0xb36431a8,0x3364b1a8,0x2e1f31a8,
0x80003400,0xb4008000,0x34000000,0x80003400,0xb400,0x34000000,0xb4008000,0xb400,0x80003400,0xb4008000,0x34000000,0x80003400,0xb400,0x34000000,0xb4008000,0xb400,
0x2e1f3400,0xb3648000,0x33640000,0x2e1f3400,0xb364b1a8,0x2e1fb1a8,0xae1f31a8,0xb364b1a8,0x33640000,0x2e1f3400,0xae1fb400,0x33640000,0xae1f31a8,0xb364b1a8,0x336431a8,0xae1f31a8,
0x31a83400,0xb1a88000,0x31a80000,0x31a83400,0xb1a88000,0xb1a8b400,0x31a83400,0xb1a88000,0xb1a8b400,0x31a80000,0xb1a88000,0xb1a8b400,0x31a80000,0x31a83400,0xb1a8b400,0x31a80000,
0x33643400,0xae1f8000,0x2e1f0000,0x33643400,0x2e1f31a8,0xb364b1a8,0x336431a8,0x2e1f31a8,0xae1f8000,0xb364b400,0x33643400,0xae1f8000,0xb364b1a8,0xae1fb1a8,0x2e1f31a8,0xb364b1a8,
0x34003400,0x80008000,0x0,0x34003400,0x34003400,0x80008000,0x0,0x34003400,0x34003400,0x80008000,0x0,0x34003400,0x34003400,0x80008000,0x0,0x34003400,
0xb364b400,0xae1f0000,0x2e1f8000,0xb364b400,0xae1fb1a8,0xb364b1a8,0x336431a8,0xae1fb1a8,0x2e1f8000,0xb364b400,0x33643400,0x2e1f8000,0x336431a8,0xae1fb1a8,0x2e1f31a8,0x336431a8,
0x31a83400,0x31a88000,0xb1a80000,0x31a83400,0xb1a80000,0x31a83400,0xb1a8b400,0xb1a80000,0xb1a8b400,0xb1a80000,0x31a88000,0xb1a8b400,0x31a88000,0xb1a8b400,0x31a83400,0x31a88000,
0xae1fb400,0xb3640000,0x33648000,0xae1fb400,0x336431a8,0x2e1fb1a8,0xae1f31a8,0x336431a8,0xb3640000,0x2e1f3400,0xae1fb400,0xb3640000,0x2e1fb1a8,0xb364b1a8,0x336431a8,0x2e1fb1a8,
0x3400,0x34008000,0xb4000000,0x3400,0x8000b400,0xb4000000,0x34008000,0x8000b400,0x3400,0x34008000,0xb4000000,0x3400,0x8000b400,0xb4000000,0x34008000,0x8000b400,
0x2e1fb400,0xb3640000,0x33648000,0x2e1fb400,0xb36431a8,0x2e1f31a8,0xae1fb1a8,0xb36431a8,0x33648000,0x2e1fb400,0xae1f3400,0x33648000,0xae1fb1a8,0xb36431a8,0x3364b1a8,0xae1fb1a8,
0xb1a83400,0x31a88000,0xb1a80000,0xb1a83400,0x31a88000,0x31a8b400,0xb1a83400,0x31a88000,0x31a8b400,0xb1a80000,0x31a88000,0x31a8b400,0xb1a80000,0xb1a83400,0x31a8b400,0xb1a80000,
0x3364b400,0xae1f0000,0x2e1f8000,0x3364b400,0x2e1fb1a8,0xb36431a8,0x3364b1a8,0x2e1fb1a8,0xae1f0000,0xb3643400,0x3364b400,0xae1f0000,0xb36431a8,0xae1f31a8,0x2e1fb1a8,0xb36431a8,
0xb4003400,0x8000,0x80000000,0xb4003400,0xb4003400,0x8000,0x80000000,0xb4003400,0xb4003400,0x8000,0x80000000,0xb4003400,0xb4003400,0x8000,0x80000000,0xb4003400,
0x3364b400,0x2e1f0000,0xae1f8000,0x3364b400,0x2e1fb1a8,0x3364b1a8,0xb36431a8,0x2e1fb1a8,0xae1f8000,0x3364b400,0xb3643400,0xae1f8000,0xb36431a8,0x2e1fb1a8,0xae1f31a8,0xb36431a8,
0xb1a83400,0xb1a88000,0x31a80000,0xb1a83400,0x31a80000,0xb1a83400,0x31a8b400,0x31a80000,0x31a8b400,0x31a80000,0xb1a88000,0x31a8b400,0xb1a88000,0x31a8b400,0xb1a83400,0xb1a88000,
0x2e1fb400,0x33640000,0xb3648000,0x2e1fb400,0xb36431a8,0xae1fb1a8,0x2e1f31a8,0xb36431a8,0x33640000,0xae1f3400,0x2e1fb400,0x33640000,0xae1fb1a8,0x3364b1a8,0xb36431a8,0xae1fb1a8,
0x80003400,0xb4008000,0x34000000,0x80003400,0xb400,0x34000000,0xb4008000,0xb400,0x80003400,0xb4008000,0x34000000,0x80003400,0xb400,0x34000000,0xb4008000,0xb400,
0xae1fb400,0x33640000,0xb3648000,0xae1fb400,0x336431a8,0xae1f31a8,0x2e1fb1a8,0x336431a8,0xb3648000,0xae1fb400,0x2e1f3400,0xb3648000,0x2e1fb1a8,0x336431a8,0xb364b1a8,0x2e1fb1a8,
0x31a83400,0xb1a88000,0x31a80000,0x31a83400,0xb1a88000,0xb1a8b400,0x31a83400,0xb1a88000,0xb1a8b400,0x31a80000,0xb1a88000,0xb1a8b400,0x31a80000,0x31a83400,0xb1a8b400,0x31a80000,
0xb364b400,0x2e1f0000,0xae1f8000,0xb364b400,0xae1fb1a8,0x336431a8,0xb364b1a8,0xae1fb1a8,0x2e1f0000,0x33643400,0xb364b400,0x2e1f0000,0x336431a8,0x2e1f31a8,0xae1fb1a8,0x336431a8,
0x0,0x80000000,0x34003400,0xb4003400,0x0,0x80000000,0x34003400,0xb4003400,0x0,0x80000000,0x34003400,0xb4003400,0x0,0x80000000,0x34003400,0xb4003400,
0xae1f0000,0x2e1f0000,0x33643400,0xb3643400,0xb364b1a8,0x3364b1a8,0x2e1f31a8,0xae1f31a8,0xb364b400,0x3364b400,0xae1f0000,0x2e1f0000,0xae1fb1a8,0x2e1fb1a8,0xb364b1a8,0x3364b1a8,
0xb1a80000,0x31a80000,0x31a83400,0xb1a83400,0xb1a8b400,0x31a8b400,0xb1a80000,0x31a80000,0x31a88000,0xb1a88000,0xb1a8b400,0x31a8b400,0x31a83400,0xb1a83400,0x31a88000,0xb1a88000,
0xb3640000,0x33640000,0x2e1f3400,0xae1f3400,0x2e1fb1a8,0xae1fb1a8,0xb364b1a8,0x3364b1a8,0x2e1f3400,0xae1f3400,0x33648000,0xb3648000,0xb364b1a8,0x3364b1a8,0xae1f31a8,0x2e1f31a8,
0xb4000000,0x34000000,0x3400,0x80003400,0x34008000,0xb4008000,0x8000b400,0xb400,0xb4000000,0x34000000,0x3400,0x80003400,0x34008000,0xb4008000,0x8000b400,0xb400,
0xb3640000,0x33640000,0xae1f3400,0x2e1f3400,0x2e1f31a8,0xae1f31a8,0x3364b1a8,0xb364b1a8,0x2e1fb400,0xae1fb400,0xb3640000,0x33640000,0xb36431a8,0x336431a8,0x2e1f31a8,0xae1f31a8,
0xb1a80000,0x31a80000,0xb1a83400,0x31a83400,0xb1a83400,0x31a83400,0x31a88000,0xb1a88000,0x31a88000,0xb1a88000,0x31a8b400,0xb1a8b400,0x31a8b400,0xb1a8b400,0xb1a80000,0x31a80000,
0xae1f0000,0x2e1f0000,0xb3643400,0x33643400,0xb36431a8,0x336431a8,0xae1f31a8,0x2e1f31a8,0xb3643400,0x33643400,0x2e1f8000,0xae1f8000,0xae1f31a8,0x2e1f31a8,0x3364b1a8,0xb364b1a8,
0x0,0x80000000,0x34003400,0xb4003400,0x0,0x80000000,0x34003400,0xb4003400,0x0,0x80000000,0x34003400,0xb4003400,0x0,0x80000000,0x34003400,0xb4003400,
0x2e1f8000,0xae1f8000,0xb364b400,0x3364b400,0x336431a8,0xb36431a8,0xae1fb1a8,0x2e1fb1a8,0x33643400,0xb3643400,0x2e1f8000,0xae1f8000,0x2e1f31a8,0xae1f31a8,0x336431a8,0xb36431a8,
0xb1a80000,0x31a80000,0x31a83400,0xb1a83400,0xb1a8b400,0x31a8b400,0xb1a80000,0x31a80000,0x31a88000,0xb1a88000,0xb1a8b400,0x31a8b400,0x31a83400,0xb1a83400,0x31a88000,0xb1a88000,
0x33648000,0xb3648000,0xae1fb400,0x2e1fb400,0xae1f31a8,0x2e1f31a8,0x336431a8,0xb36431a8,0xae1fb400,0x2e1fb400,0xb3640000,0x33640000,0x336431a8,0xb36431a8,0x2e1fb1a8,0xae1fb1a8,
0xb4000000,0x34000000,0x3400,0x80003400,0x34008000,0xb4008000,0x8000b400,0xb400,0xb4000000,0x34000000,0x3400,0x80003400,0x34008000,0xb4008000,0x8000b400,0xb400,
0x33648000,0xb3648000,0x2e1fb400,0xae1fb400,0xae1fb1a8,0x2e1fb1a8,0xb36431a8,0x336431a8,0xae1f3400,0x2e1f3400,0x33648000,0xb3648000,0x3364b1a8,0xb364b1a8,0xae1fb1a8,0x2e1fb1a8,
0xb1a80000,0x31a80000,0xb1a83400,0x31a83400,0xb1a83400,0x31a83400,0x31a88000,0xb1a88000,0x31a88000,0xb1a88000,0x31a8b400,0xb1a8b400,0x31a8b400,0xb1a8b400,0xb1a80000,0x31a80000,
0x2e1f8000,0xae1f8000,0x3364b400,0xb364b400,0x3364b1a8,0xb364b1a8,0x2e1fb1a8,0xae1fb1a8,0x3364b400,0xb364b400,0xae1f0000,0x2e1f0000,0x2e1fb1a8,0xae1fb1a8,0xb36431a8,0x336431a8,
0x0,0x34003400,0x0,0x34003400,0x0,0x34003400,0x0,0x34003400,0x0,0x34003400,0x0,0x34003400,0x0,0x34003400,0x0,0x34003400,
0xae1f0000,0x33643400,0x2e1f8000,0xb364b400,0xb364b1a8,0x2e1f31a8,0x336431a8,0xae1fb1a8,0xb364b400,0xae1f0000,0x33643400,0x2e1f8000,0xae1fb1a8,0xb364b1a8,0x2e1f31a8,0x336431a8,
0xb1a80000,0x31a83400,0xb1a80000,0x31a83400,0xb1a8b400,0xb1a80000,0xb1a8b400,0xb1a80000,0x31a88000,0xb1a8b400,0x31a88000,0xb1a8b400,0x31a83400,0x31a88000,0x31a83400,0x31a88000,
0xb3640000,0x2e1f3400,0x33648000,0xae1fb400,0x2e1fb1a8,0xb364b1a8,0xae1f31a8,0x336431a8,0x2e1f3400,0x33648000,0xae1fb400,0xb3640000,0xb364b1a8,0xae1f31a8,0x336431a8,0x2e1fb1a8,
0xb4000000,0x3400,0xb4000000,0x3400,0x34008000,0x8000b400,0x34008000,0x8000b400,0xb4000000,0x3400,0xb4000000,0x3400,0x34008000,0x8000b400,0x34008000,0x8000b400,
0xb3640000,0xae1f3400,0x33648000,0x2e1fb400,0x2e1f31a8,0x3364b1a8,0xae1fb1a8,0xb36431a8,0x2e1fb400,0xb3640000,0xae1f3400,0x33648000,0xb36431a8,0x2e1f31a8,0x3364b1a8,0xae1fb1a8,
0xb1a80000,0xb1a83400,0xb1a80000,0xb1a83400,0xb1a83400,0x31a88000,0xb1a83400,0x31a88000,0x31a88000,0x31a8b400,0x31a88000,0x31a8b400,0x31a8b400,0xb1a80000,0x31a8b400,0xb1a80000,
0xae1f0000,0xb3643400,0x2e1f8000,0x3364b400,0xb36431a8,0xae1f31a8,0x3364b1a8,0x2e1fb1a8,0xb3643400,0x2e1f8000,0x3364b400,0xae1f0000,0xae1f31a8,0x3364b1a8,0x2e1fb1a8,0xb36431a8,
0x80000000,0xb4003400,0x80000000,0xb4003400,0x80000000,0xb4003400,0x80000000,0xb4003400,0x80000000,0xb4003400,0x80000000,0xb4003400,0x80000000,0xb4003400,0x80000000,0xb4003400,
0x2e1f0000,0xb3643400,0xae1f8000,0x3364b400,0x3364b1a8,0xae1f31a8,0xb36431a8,0x2e1fb1a8,0x3364b400,0x2e1f0000,0xb3643400,0xae1f8000,0x2e1fb1a8,0x3364b1a8,0xae1f31a8,0xb36431a8,
0x31a80000,0xb1a83400,0x31a80000,0xb1a83400,0x31a8b400,0x31a80000,0x31a8b400,0x31a80000,0xb1a88000,0x31a8b400,0xb1a88000,0x31a8b400,0xb1a83400,0xb1a88000,0xb1a83400,0xb1a88000,
0x33640000,0xae1f3400,0xb3648000,0x2e1fb400,0xae1fb1a8,0x3364b1a8,0x2e1f31a8,0xb36431a8,0xae1f3400,0xb3648000,0x2e1fb400,0x33640000,0x3364b1a8,0x2e1f31a8,0xb36431a8,0xae1fb1a8,
0x34000000,0x80003400,0x34000000,0x80003400,0xb4008000,0xb400,0xb4008000,0xb400,0x34000000,0x80003400,0x34000000,0x80003400,0xb4008000,0xb400,0xb4008000,0xb400,
0x33640000,0x2e1f3400,0xb3648000,0xae1fb400,0xae1f31a8,0xb364b1a8,0x2e1fb1a8,0x336431a8,0xae1fb400,0x33640000,0x2e1f3400,0xb3648000,0x336431a8,0xae1f31a8,0xb364b1a8,0x2e1fb1a8,
0x31a80000,0x31a83400,0x31a80000,0x31a83400,0x31a83400,0xb1a88000,0x31a83400,0xb1a88000,0xb1a88000,0xb1a8b400,0xb1a88000,0xb1a8b400,0xb1a8b400,0x31a80000,0xb1a8b400,0x31a80000,
0x2e1f0000,0x33643400,0xae1f8000,0xb364b400,0x336431a8,0x2e1f31a8,0xb364b1a8,0xae1fb1a8,0x33643400,0xae1f8000,0xb364b400,0x2e1f0000,0x2e1f31a8,0xb364b1a8,0xae1fb1a8,0x336431a8,
0x0,0x34003400,0x0,0x38003800,0x0,0x34003400,0x0,0x38003800,0x0,0x34003400,0x0,0x38003800,0x0,0x34003400,0x0,0x38003800,
0xb1a80000,0x31a83400,0xb5a80000,0x35a83800,0xb1a8b400,0xb1a80000,0xb5a8b800,0xb5a80000,0x31a88000,0xb1a8b400,0x35a88000,0xb5a8b800,0x31a83400,0x31a88000,0x35a83800,0x35a88000,
0xb4000000,0x3400,0xb8000000,0x3800,0x34008000,0x8000b400,0x38008000,0x8000b800,0xb4000000,0x3400,0xb8000000,0x3800,0x34008000,0x8000b400,0x38008000,0x8000b800,
0xb1a80000,0xb1a83400,0xb5a80000,0xb5a83800,0xb1a83400,0x31a88000,0xb5a83800,0x35a88000,0x31a88000,0x31a8b400,0x35a88000,0x35a8b800,0x31a8b400,0xb1a80000,0x35a8b800,0xb5a80000,
0x80000000,0xb4003400,0x80000000,0xb8003800,0x80000000,0xb4003400,0x80000000,0xb8003800,0x80000000,0xb4003400,0x80000000,0xb8003800,0x80000000,0xb4003400,0x80000000,0xb8003800,
0x31a80000,0xb1a83400,0x35a80000,0xb5a83800,0x31a8b400,0x31a80000,0x35a8b800,0x35a80000,0xb1a88000,0x31a8b400,0xb5a88000,0x35a8b800,0xb1a83400,0xb1a88000,0xb5a83800,0xb5a88000,
0x34000000,0x80003400,0x38000000,0x80003800,0xb4008000,0xb400,0xb8008000,0xb800,0x34000000,0x80003400,0x38000000,0x80003800,0xb4008000,0xb400,0xb8008000,0xb800,
0x31a80000,0x31a83400,0x35a80000,0x35a83800,0x31a83400,0xb1a88000,0x35a83800,0xb5a88000,0xb1a88000,0xb1a8b400,0xb5a88000,0xb5a8b800,0xb1a8b400,0x31a80000,0xb5a8b800,0x35a80000,
0x0,0x1e489e48,0x34003400,0xb3ff33ff,0x0,0x1e489e48,0x34003400,0xb3ff33ff,0x0,0x1e489e48,0x34003400,0xb3ff33ff,0x0,0x1e489e48,0x34003400,0xb3ff33ff,
0xae2b9248,0x2e879f11,0x33623400,0xb34e33ff,0xb367b1ad,0x3379b1d0,0x2e1431a4,0xadb63180,0xb362b400,0x334eb3ff,0xae2b9248,0x2e879f11,0xae14b1a4,0x2db6b180,0xb367b1ad,0x3379b1d0,
0xb1b19648,0x31d49fda,0x319f3400,0xb17b33ff,0xb19fb400,0x317bb3ff,0xb1b19648,0x31d49fda,0x31b11648,0xb1d41fda,0xb19fb400,0x317bb3ff,0x319f3400,0xb17b33ff,0x31b11648,0xb1d41fda,
0xb36b98b6,0x337da052,0x2dfd3400,0xad9f33ff,0x2e42b19b,0xae9eb176,0xb35db1b5,0x3349b1d8,0x2dfd3400,0xad9f33ff,0x336b18b6,0xb37d2052,0xb35db1b5,0x3349b1d8,0xae42319b,0x2e9e3176,
0xb4009a48,0x33ffa0b6,0x9a483400,0x20b633ff,0x34001a48,0xb3ff20b6,0x1a48b400,0xa0b6b3ff,0xb4009a48,0x33ffa0b6,0x9a483400,0x20b633ff,0x34001a48,0xb3ff20b6,0x1a48b400,0xa0b6b3ff,
0xb3589bdb,0x3343a11b,0xae593400,0x2eb533fe,0x2de531be,0xad8731e1,0x3370b192,0xb382b16d,0x2e59b400,0xaeb5b3fe,0xb3589bdb,0x3343a11b,0xb3703192,0x3382316d,0x2de531be,0xad8731e1,
0xb18d9cb6,0x3169a17f,0xb1c33400,0x31e533fe,0xb1c33400,0x31e533fe,0x318d1cb6,0xb169217f,0x318d1cb6,0xb169217f,0x31c3b400,0xb1e5b3fe,0x31c3b400,0xb1e5b3fe,0xb18d9cb6,0x3169a17f,
0xadce9d7f,0x2d70a1e3,0xb3743400,0x338633fe,0xb3533189,0x333e3164,0xae7031c7,0x2ecc31e9,0xb3743400,0x338633fe,0x2dce1d7f,0xad7021e3,0xae7031c7,0x2ecc31e9,0x3353b189,0xb33eb164,
0x0,0x1e489e48,0x34003400,0xb3ff33ff,0x0,0x1e489e48,0x34003400,0xb3ff33ff,0x0,0x1e489e48,0x34003400,0xb3ff33ff,0x0,0x1e489e48,0x34003400,0xb3ff33ff,
0x2e2b1248,0xae871f11,0xb362b400,0x334eb3ff,0x336731ad,0xb37931d0,0xae14b1a4,0x2db6b180,0x33623400,0xb34e33ff,0x2e2b1248,0xae871f11,0x2e1431a4,0xadb63180,0x336731ad,0xb37931d0,
0xb1b19648,0x31d49fda,0x319f3400,0xb17b33ff,0xb19fb400,0x317bb3ff,0xb1b19648,0x31d49fda,0x31b11648,0xb1d41fda,0xb19fb400,0x317bb3ff,0x319f3400,0xb17b33ff,0x31b11648,0xb1d41fda,
0x336b18b6,0xb37d2052,0xadfdb400,0x2d9fb3ff,0xae42319b,0x2e9e3176,0x335d31b5,0xb34931d8,0xadfdb400,0x2d9fb3ff,0xb36b98b6,0x337da052,0x335d31b5,0xb34931d8,0x2e42b19b,0xae9eb176,
0xb4009a48,0x33ffa0b6,0x9a483400,0x20b633ff,0x34001a48,0xb3ff20b6,0x1a48b400,0xa0b6b3ff,0xb4009a48,0x33ffa0b6,0x9a483400,0x20b633ff,0x34001a48,0xb3ff20b6,0x1a48b400,0xa0b6b3ff,
0x33581bdb,0xb343211b,0x2e59b400,0xaeb5b3fe,0xade5b1be,0x2d87b1e1,0xb3703192,0x3382316d,0xae593400,0x2eb533fe,0x33581bdb,0xb343211b,0x3370b192,0xb382b16d,0xade5b1be,0x2d87b1e1,
0xb18d9cb6,0x3169a17f,0xb1c33400,0x31e533fe,0xb1c33400,0x31e533fe,0x318d1cb6,0xb169217f,0x318d1cb6,0xb169217f,0x31c3b400,0xb1e5b3fe,0x31c3b400,0xb1e5b3fe,0xb18d9cb6,0x3169a17f,
0x2dce1d7f,0xad7021e3,0x3374b400,0xb386b3fe,0x3353b189,0xb33eb164,0x2e70b1c7,0xaeccb1e9,0x3374b400,0xb386b3fe,0xadce9d7f,0x2d70a1e3,0x2e70b1c7,0xaeccb1e9,0xb3533189,0x333e3164,
0x92480000,0x34003400,0x9f119e48,0x33ff33ff,0x98b69648,0x34003400,0xa0529fda,0x33ff33ff,0x9bdb9a48,0x34003400,0xa11ba0b6,0x33fe33ff,0x9d7f9cb6,0x34003400,0xa1e3a17f,0x33fe33fe,
0xae2b0000,0x33623400,0x2e871e48,0xb34eb3ff,0xb36bb1b1,0x2dfd319f,0x337d31d4,0xad9fb17b,0xb358b400,0xae599a48,0x334333ff,0x2eb520b6,0xadceb18d,0xb374b1c3,0x2d703169,0x338631e5,
0xb1ad0000,0x31a43400,0xb1d09e48,0x318033ff,0xb19bb400,0xb1b59648,0xb176b3ff,0xb1d89fda,0x31be1a48,0xb192b400,0x31e120b6,0xb16db3ff,0x31893400,0x31c71cb6,0x316433fe,0x31e9217f,
0xb3670000,0x2e143400,0x33791e48,0xadb6b3ff,0x2e42b19f,0xb35db1b1,0xae9e317b,0x334931d4,0x2de53400,0x33701a48,0xad87b3ff,0xb382a0b6,0xb353b1c3,0xae70318d,0x333e31e5,0x2eccb169,
0xb4000000,0x92483400,0xb3ff9e48,0x9f1133ff,0x34001648,0x18b6b400,0x33ff1fda,0x2052b3ff,0xb4009a48,0x9bdb3400,0xb3fea0b6,0xa11b33ff,0x34001cb6,0x1d7fb400,0x33fe217f,0x21e3b3fe,
0xb3620000,0xae2b3400,0x334e1e48,0x2e87b3ff,0x2dfd31b1,0x336bb19f,0xad9fb1d4,0xb37d317b,0x2e59b400,0xb3589a48,0xaeb533ff,0x334320b6,0xb374318d,0x2dce31c3,0x3386b169,0xad70b1e5,
0xb1a40000,0xb1ad3400,0xb1809e48,0xb1d033ff,0xb1b53400,0x319b1648,0xb1d833ff,0x31761fda,0x31921a48,0x31beb400,0x316d20b6,0x31e1b3ff,0x31c7b400,0xb1899cb6,0x31e9b3fe,0xb164a17f,
0xae140000,0xb3673400,0x2db61e48,0x3379b3ff,0xb35d319f,0xae4231b1,0x3349b17b,0x2e9eb1d4,0xb3703400,0x2de51a48,0x3382b3ff,0xad87a0b6,0xae7031c3,0x3353b18d,0x2eccb1e5,0xb33e3169,
0x12480000,0xb4003400,0x1f119e48,0xb3ff33ff,0x18b69648,0xb4003400,0x20529fda,0xb3ff33ff,0x1bdb9a48,0xb4003400,0x211ba0b6,0xb3fe33ff,0x1d7f9cb6,0xb4003400,0x21e3a17f,0xb3fe33fe,
0x2e2b0000,0xb3623400,0xae871e48,0x334eb3ff,0x336bb1b1,0xadfd319f,0xb37d31d4,0x2d9fb17b,0x3358b400,0x2e599a48,0xb34333ff,0xaeb520b6,0x2dceb18d,0x3374b1c3,0xad703169,0xb38631e5,
0x31ad0000,0xb1a43400,0x31d09e48,0xb18033ff,0x319bb400,0x31b59648,0x3176b3ff,0x31d89fda,0xb1be1a48,0x3192b400,0xb1e120b6,0x316db3ff,0xb1893400,0xb1c71cb6,0xb16433fe,0xb1e9217f,
0x33670000,0xae143400,0xb3791e48,0x2db6b3ff,0xae42b19f,0x335db1b1,0x2e9e317b,0xb34931d4,0xade53400,0xb3701a48,0x2d87b3ff,0x3382a0b6,0x3353b1c3,0x2e70318d,0xb33e31e5,0xaeccb169,
0x34000000,0x12483400,0x33ff9e48,0x1f1133ff,0xb4001648,0x98b6b400,0xb3ff1fda,0xa052b3ff,0x34009a48,0x1bdb3400,0x33fea0b6,0x211b33ff,0xb4001cb6,0x9d7fb400,0xb3fe217f,0xa1e3b3fe,
0x33620000,0x2e2b3400,0xb34e1e48,0xae87b3ff,0xadfd31b1,0xb36bb19f,0x2d9fb1d4,0x337d317b,0xae59b400,0x33589a48,0x2eb533ff,0xb34320b6,0x3374318d,0xadce31c3,0xb386b169,0x2d70b1e5,
0x31a40000,0x31ad3400,0x31809e48,0x31d033ff,0x31b53400,0xb19b1648,0x31d833ff,0xb1761fda,0xb1921a48,0xb1beb400,0xb16d20b6,0xb1e1b3ff,0xb1c7b400,0x31899cb6,0xb1e9b3fe,0x3164a17f,
0x2e140000,0x33673400,0xadb61e48,0xb379b3ff,0x335d319f,0x2e4231b1,0xb349b17b,0xae9eb1d4,0x33703400,0xade51a48,0xb382b3ff,0x2d87a0b6,0x2e7031c3,0xb353b18d,0xaeccb1e5,0x333e3169,
0x0,0x34003400,0xa6480000,0x37fe3800,0x0,0x34003400,0xacb2aa46,0x37ea37f6,0x0,0x34003400,0xafc6ae3e,0x37c337d9,0x0,0x34003400,0xb164b0a5,0x378837a8,
0xb1eda248,0x315f33fe,0xb5ed0000,0x355f3800,0xb15fb3fe,0xb1eda248,0xb4c4b7f6,0xb66daa46,0x31ed2248,0xb15fb3fe,0x36dd2e3e,0xb41db7d9,0x315f33fe,0x31ed2248,0x32d737a8,0x373b30a5,
0xb3f6a646,0xa64633f6,0xb7fe0000,0xa6483800,0x33f62646,0x2646b3f6,0x37ea2a46,0x2cb2b7f6,0xb3f6a646,0xa64633f6,0xb7c3ae3e,0xafc637d9,0x33f62646,0x2646b3f6,0x378830a5,0x3164b7a8,
0xb0c4a8b2,0xb26d33ea,0xb55f0000,0xb5ed3800,0xb26d33ea,0x30c428b2,0xb66d37f6,0x34c42a46,0x30c428b2,0x326db3ea,0x341d2e3e,0x36ddb7d9,0x326db3ea,0xb0c4a8b2,0x373bb7a8,0xb2d7b0a5,
0x2a3eaa3e,0xb3d933d9,0x26480000,0xb7fe3800,0x2a3eaa3e,0xb3d933d9,0x2cb2aa46,0xb7ea37f6,0x2a3eaa3e,0xb3d933d9,0x2fc6ae3e,0xb7c337d9,0x2a3eaa3e,0xb3d933d9,0x3164b0a5,0xb78837a8,
0x32ddabc6,0xb01d33c3,0x35ed0000,0xb55f3800,0x301db3c3,0x32ddabc6,0x34c4b7f6,0x366daa46,0xb2dd2bc6,0x301db3c3,0xb6dd2e3e,0x341db7d9,0xb01d33c3,0xb2dd2bc6,0xb2d737a8,0xb73b30a5,
0x33a8aca5,0x2ca533a8,0x37fe0000,0x26483800,0xb3a82ca5,0xaca5b3a8,0xb7ea2a46,0xacb2b7f6,0x33a8aca5,0x2ca533a8,0x37c3ae3e,0x2fc637d9,0xb3a82ca5,0xaca5b3a8,0xb78830a5,0xb164b7a8,
0x2ed7ad64,0x333b3388,0x355f0000,0x35ed3800,0x333b3388,0xaed72d64,0x366d37f6,0xb4c42a46,0xaed72d64,0xb33bb388,0xb41d2e3e,0xb6ddb7d9,0xb33bb388,0x2ed7ad64,0xb73bb7a8,0x32d7b0a5,
0x0,0x2248a248,0x34003400,0xb3fe33fe,0x0,0x2248a248,0x34003400,0xb3fe33fe,0x0,0x2248a248,0x34003400,0xb3fe33fe,0x0,0x2248a248,0x34003400,0xb3fe33fe,
0xae379648,0x2eeea311,0x335f3400,0xb33633fd,0xb369b1b1,0x338cb1f6,0x2e08319f,0xad4c3156,0xb35fb400,0x3336b3fd,0xae379648,0x2eeea311,0xae08b19f,0x2d4cb156,0xb369b1b1,0x338cb1f6,
0xb1ba9a48,0x31fea3d9,0x31963400,0xb14d33fc,0xb196b400,0x314db3fc,0xb1ba9a48,0x31fea3d9,0x31ba1a48,0xb1fe23d9,0xb196b400,0x314db3fc,0x31963400,0xb14d33fc,0x31ba1a48,0xb1fe23d9,
0xb3729cb6,0x3395a451,0x2dda3400,0xad1d33fb,0x2e65b18d,0xaf1bb143,0xb355b1c3,0x332bb207,0x2dda3400,0xad1d33fb,0x33721cb6,0xb3952451,0xb355b1c3,0x332bb207,0xae65318d,0x2f1b3143,
0xb3ff9e48,0x33faa4b5,0x9e4833ff,0x24b533fa,0x33ff1e48,0xb3fa24b5,0x1e48b3ff,0xa4b5b3fa,0xb3ff9e48,0x33faa4b5,0x9e4833ff,0x24b533fa,0x33ff1e48,0xb3fa24b5,0x1e48b3ff,0xa4b5b3fa,
0xb34b9fda,0x3320a51a,0xae9333ff,0x2f4833f9,0x2dab31d4,0xaced3217,0x337bb17b,0xb39db130,0x2e93b3ff,0xaf48b3f9,0xb34b9fda,0x3320a51a,0xb37b317b,0x339d3130,0x2dab31d4,0xaced3217,
0xb172a0b6,0x3127a57e,0xb1dc33ff,0x321f33f8,0xb1dc33ff,0x321f33f8,0x317220b6,0xb127257e,0x317220b6,0xb127257e,0x31dcb3ff,0xb21fb3f8,0x31dcb3ff,0xb21fb3f8,0xb172a0b6,0x3127a57e,
0xad7ca17f,0x2cbda5e2,0xb38433fe,0x33a433f7,0xb3413169,0x3314311d,0xaec131e5,0x2f753227,0xb38433fe,0x33a433f7,0x2d7c217f,0xacbd25e2,0xaec131e5,0x2f753227,0x3341b169,0xb314b11d,
0x0,0x2248a248,0x34003400,0xb3fe33fe,0x0,0x2248a248,0x34003400,0xb3fe33fe,0x0,0x2248a248,0x34003400,0xb3fe33fe,0x0,0x2248a248,0x34003400,0xb3fe33fe,
0x2e371648,0xaeee2311,0xb35fb400,0x3336b3fd,0x336931b1,0xb38c31f6,0xae08b19f,0x2d4cb156,0x335f3400,0xb33633fd,0x2e371648,0xaeee2311,0x2e08319f,0xad4c3156,0x336931b1,0xb38c31f6,
0xb1ba9a48,0x31fea3d9,0x31963400,0xb14d33fc,0xb196b400,0x314db3fc,0xb1ba9a48,0x31fea3d9,0x31ba1a48,0xb1fe23d9,0xb196b400,0x314db3fc,0x31963400,0xb14d33fc,0x31ba1a48,0xb1fe23d9,
0x33721cb6,0xb3952451,0xaddab400,0x2d1db3fb,0xae65318d,0x2f1b3143,0x335531c3,0xb32b3207,0xaddab400,0x2d1db3fb,0xb3729cb6,0x3395a451,0x335531c3,0xb32b3207,0x2e65b18d,0xaf1bb143,
0xb3ff9e48,0x33faa4b5,0x9e4833ff,0x24b533fa,0x33ff1e48,0xb3fa24b5,0x1e48b3ff,0xa4b5b3fa,0xb3ff9e48,0x33faa4b5,0x9e4833ff,0x24b533fa,0x33ff1e48,0xb3fa24b5,0x1e48b3ff,0xa4b5b3fa,
0x334b1fda,0xb320251a,0x2e93b3ff,0xaf48b3f9,0xadabb1d4,0x2cedb217,0xb37b317b,0x339d3130,0xae9333ff,0x2f4833f9,0x334b1fda,0xb320251a,0x337bb17b,0xb39db130,0xadabb1d4,0x2cedb217,
0xb172a0b6,0x3127a57e,0xb1dc33ff,0x321f33f8,0xb1dc33ff,0x321f33f8,0x317220b6,0xb127257e,0x317220b6,0xb127257e,0x31dcb3ff,0xb21fb3f8,0x31dcb3ff,0xb21fb3f8,0xb172a0b6,0x3127a57e,
0x2d7c217f,0xacbd25e2,0x3384b3fe,0xb3a4b3f7,0x3341b169,0xb314b11d,0x2ec1b1e5,0xaf75b227,0x3384b3fe,0xb3a4b3f7,0xad7ca17f,0x2cbda5e2,0x2ec1b1e5,0xaf75b227,0xb3413169,0x3314311d,
0x96480000,0x34003400,0xa311a248,0x33fd33fe,0x9cb69a48,0x34003400,0xa451a3d9,0x33fb33fc,0x9fda9e48,0x33ff33ff,0xa51aa4b5,0x33f933fa,0xa17fa0b6,0x33fe33ff,0xa5e2a57e,0x33f733f8,
0xae370000,0x335f3400,0x2eee2248,0xb336b3fe,0xb372b1ba,0x2dda3196,0x339531fe,0xad1db14d,0xb34bb3ff,0xae939e48,0x332033fa,0x2f4824b5,0xad7cb172,0xb384b1dc,0x2cbd3127,0x33a4321f,
0xb1b10000,0x319f3400,0xb1f6a248,0x315633fe,0xb18db400,0xb1c39a48,0xb143b3fc,0xb207a3d9,0x31d41e48,0xb17bb3ff,0x321724b5,0xb130b3fa,0x316933ff,0x31e520b6,0x311d33f8,0x3227257e,
0xb3690000,0x2e083400,0x338c2248,0xad4cb3fe,0x2e65b196,0xb355b1ba,0xaf1b314d,0x332b31fe,0x2dab33ff,0x337b1e48,0xacedb3fa,0xb39da4b5,0xb341b1dc,0xaec13172,0x3314321f,0x2f75b127,
0xb4000000,0x96483400,0xb3fda248,0xa31133fe,0x34001a48,0x1cb6b400,0x33fb23d9,0x2451b3fc,0xb3ff9e48,0x9fda33ff,0xb3f9a4b5,0xa51a33fa,0x33fe20b6,0x217fb3ff,0x33f7257e,0x25e2b3f8,
0xb35f0000,0xae373400,0x33362248,0x2eeeb3fe,0x2dda31ba,0x3372b196,0xad1db1fe,0xb395314d,0x2e93b3ff,0xb34b9e48,0xaf4833fa,0x332024b5,0xb3843172,0x2d7c31dc,0x33a4b127,0xacbdb21f,
0xb19f0000,0xb1b13400,0xb156a248,0xb1f633fe,0xb1c33400,0x318d1a48,0xb20733fc,0x314323d9,0x317b1e48,0x31d4b3ff,0x313024b5,0x3217b3fa,0x31e5b3ff,0xb169a0b6,0x3227b3f8,0xb11da57e,
0xae080000,0xb3693400,0x2d4c2248,0x338cb3fe,0xb3553196,0xae6531ba,0x332bb14d,0x2f1bb1fe,0xb37b33ff,0x2dab1e48,0x339db3fa,0xaceda4b5,0xaec131dc,0x3341b172,0x2f75b21f,0xb3143127,
0x16480000,0xb4003400,0x2311a248,0xb3fd33fe,0x1cb69a48,0xb4003400,0x2451a3d9,0xb3fb33fc,0x1fda9e48,0xb3ff33ff,0x251aa4b5,0xb3f933fa,0x217fa0b6,0xb3fe33ff,0x25e2a57e,0xb3f733f8,
0x2e370000,0xb35f3400,0xaeee2248,0x3336b3fe,0x3372b1ba,0xadda3196,0xb39531fe,0x2d1db14d,0x334bb3ff,0x2e939e48,0xb32033fa,0xaf4824b5,0x2d7cb172,0x3384b1dc,0xacbd3127,0xb3a4321f,
0x31b10000,0xb19f3400,0x31f6a248,0xb15633fe,0x318db400,0x31c39a48,0x3143b3fc,0x3207a3d9,0xb1d41e48,0x317bb3ff,0xb21724b5,0x3130b3fa,0xb16933ff,0xb1e520b6,0xb11d33f8,0xb227257e,
0x33690000,0xae083400,0xb38c2248,0x2d4cb3fe,0xae65b196,0x3355b1ba,0x2f1b314d,0xb32b31fe,0xadab33ff,0xb37b1e48,0x2cedb3fa,0x339da4b5,0x3341b1dc,0x2ec13172,0xb314321f,0xaf75b127,
0x34000000,0x16483400,0x33fda248,0x231133fe,0xb4001a48,0x9cb6b400,0xb3fb23d9,0xa451b3fc,0x33ff9e48,0x1fda33ff,0x33f9a4b5,0x251a33fa,0xb3fe20b6,0xa17fb3ff,0xb3f7257e,0xa5e2b3f8,
0x335f0000,0x2e373400,0xb3362248,0xaeeeb3fe,0xadda31ba,0xb372b196,0x2d1db1fe,0x3395314d,0xae93b3ff,0x334b9e48,0x2f4833fa,0xb32024b5,0x33843172,0xad7c31dc,0xb3a4b127,0x2cbdb21f,
0x319f0000,0x31b13400,0x3156a248,0x31f633fe,0x31c33400,0xb18d1a48,0x320733fc,0xb14323d9,0xb17b1e48,0xb1d4b3ff,0xb13024b5,0xb217b3fa,0xb1e5b3ff,0x3169a0b6,0xb227b3f8,0x311da57e,
0x2e080000,0x33693400,0xad4c2248,0xb38cb3fe,0x33553196,0x2e6531ba,0xb32bb14d,0xaf1bb1fe,0x337b33ff,0xadab1e48,0xb39db3fa,0x2ceda4b5,0x2ec131dc,0xb341b172,0xaf75b21f,0x33143127,
0x0,0x34003400,0xaa460000,0x37f63800,0x0,0x34003400,0xb0a5ae3e,0x37a837d9,0x0,0x34003400,0xb38bb21f,0x370e3764,0x0,0x34003400,0xb513b472,0x362f36a7,
0xb22fa646,0x311333f6,0xb62f0000,0x35133800,0xb113b3f6,0xb22fa646,0xb38bb7d9,0xb70eae3e,0x322f2646,0xb113b3f6,0x37a8321f,0xb0a5b764,0x311333f6,0x322f2646,0x2a4636a7,0x37f63472,
0xb3d9aa3e,0xaa3e33d9,0xb7f60000,0xaa463800,0x33d92a3e,0x2a3eb3d9,0x37a82e3e,0x30a5b7d9,0xb3d9aa3e,0xaa3e33d9,0xb70eb21f,0xb38b3764,0x33d92a3e,0x2a3eb3d9,0x362f3472,0x3513b6a7,
0xaf8baca5,0xb30e33a8,0xb5130000,0xb62f3800,0xb30e33a8,0x2f8b2ca5,0xb70e37d9,0x338b2e3e,0x2f8b2ca5,0x330eb3a8,0x30a5321f,0x37a8b764,0x330eb3a8,0xaf8baca5,0x37f6b6a7,0xaa46b472,
0x2e1fae1f,0xb3643364,0x2a460000,0xb7f63800,0x2e1fae1f,0xb3643364,0x30a5ae3e,0xb7a837d9,0x2e1fae1f,0xb3643364,0x338bb21f,0xb70e3764,0x2e1fae1f,0xb3643364,0x3513b472,0xb62f36a7,
0x33a8af8b,0xaca5330e,0x362f0000,0xb5133800,0x2ca5b30e,0x33a8af8b,0x338bb7d9,0x370eae3e,0xb3a82f8b,0x2ca5b30e,0xb7a8321f,0x30a5b764,0xaca5330e,0xb3a82f8b,0xaa4636a7,0xb7f63472,
0x32a7b072,0x307232a7,0x37f60000,0x2a463800,0xb2a73072,0xb072b2a7,0xb7a82e3e,0xb0a5b7d9,0x32a7b072,0x307232a7,0x370eb21f,0x338b3764,0xb2a73072,0xb072b2a7,0xb62f3472,0xb513b6a7,
0x2646b113,0x33f6322f,0x35130000,0x362f3800,0x33f6322f,0xa6463113,0x370e37d9,0xb38b2e3e,0xa6463113,0xb3f6b22f,0xb0a5321f,0xb7a8b764,0xb3f6b22f,0x2646b113,0xb7f6b6a7,0x2a46b472,
0x0,0x24b5a4b5,0x34003400,0xb3fa33fa,0x0,0x24b5a4b5,0x34003400,0xb3fa33fa,0x0,0x24b5a4b5,0x34003400,0xb3fa33fa,0x0,0x24b5a4b5,0x34003400,0xb3fa33fa,
0xae4298b6,0x2f53a54c,0x335d3400,0xb31d33f9,0xb36bb1b5,0x339eb21b,0x2dfd319b,0xace1312b,0xb35db400,0x331db3f9,0xae4298b6,0x2f53a54c,0xadfdb19b,0x2ce1b12b,0xb36bb1b5,0x339eb21b,
0xb1c39cb6,0x3227a5e2,0x318d3400,0xb11d33f7,0xb18db400,0x311db3f7,0xb1c39cb6,0x3227a5e2,0x31c31cb6,0xb22725e2,0xb18db400,0x311db3f7,0x318d3400,0xb11d33f7,0x31c31cb6,0xb22725e2,
0xb3799f11,0x33aaa678,0x2db633ff,0xac9933f6,0x2e87b180,0xaf96b10e,0xb34eb1d0,0x330bb233,0x2db633ff,0xac9933f6,0x33791f11,0xb3aa2678,0xb34eb1d0,0x330bb233,0xae873180,0x2f96310e,
0xb3ffa0b6,0x33f4a70e,0xa0b633ff,0x270e33f4,0x33ff20b6,0xb3f4270e,0x20b6b3ff,0xa70eb3f4,0xb3ffa0b6,0x33f4a70e,0xa0b633ff,0x270e33f4,0x33ff20b6,0xb3f4270e,0x20b6b3ff,0xa70eb3f4,
0xb33ea1e3,0x32f9a7a4,0xaecc33fe,0x2fd833f1,0x2d7031e9,0xac51324b,0x3386b164,0xb3b4b0f1,0x2eccb3fe,0xafd8b3f1,0xb33ea1e3,0x32f9a7a4,0xb3863164,0x33b430f1,0x2d7031e9,0xac51324b,
0xb156a311,0x30e2a81d,0xb1f633fd,0x325633ef,0xb1f633fd,0x325633ef,0x31562311,0xb0e2281d,0x31562311,0xb0e2281d,0x31f6b3fd,0xb256b3ef,0x31f6b3fd,0xb256b3ef,0xb156a311,0x30e2a81d,
0xad29a41f,0x2c08a867,0xb39333fc,0x33be33ed,0xb32e3148,0x32e630d3,0xaf103202,0x300d3262,0xb39333fc,0x33be33ed,0x2d29241f,0xac082867,0xaf103202,0x300d3262,0x332eb148,0xb2e6b0d3,
0x0,0x24b5a4b5,0x34003400,0xb3fa33fa,0x0,0x24b5a4b5,0x34003400,0xb3fa33fa,0x0,0x24b5a4b5,0x34003400,0xb3fa33fa,0x0,0x24b5a4b5,0x34003400,0xb3fa33fa,
0x2e4218b6,0xaf53254c,0xb35db400,0x331db3f9,0x336b31b5,0xb39e321b,0xadfdb19b,0x2ce1b12b,0x335d3400,0xb31d33f9,0x2e4218b6,0xaf53254c,0x2dfd319b,0xace1312b,0x336b31b5,0xb39e321b,
0xb1c39cb6,0x3227a5e2,0x318d3400,0xb11d33f7,0xb18db400,0x311db3f7,0xb1c39cb6,0x3227a5e2,0x31c31cb6,0xb22725e2,0xb18db400,0x311db3f7,0x318d3400,0xb11d33f7,0x31c31cb6,0xb22725e2,
0x33791f11,0xb3aa2678,0xadb6b3ff,0x2c99b3f6,0xae873180,0x2f96310e,0x334e31d0,0xb30b3233,0xadb6b3ff,0x2c99b3f6,0xb3799f11,0x33aaa678,0x334e31d0,0xb30b3233,0x2e87b180,0xaf96b10e,
0xb3ffa0b6,0x33f4a70e,0xa0b633ff,0x270e33f4,0x33ff20b6,0xb3f4270e,0x20b6b3ff,0xa70eb3f4,0xb3ffa0b6,0x33f4a70e,0xa0b633ff,0x270e33f4,0x33ff20b6,0xb3f4270e,0x20b6b3ff,0xa70eb3f4,
0x333e21e3,0xb2f927a4,0x2eccb3fe,0xafd8b3f1,0xad70b1e9,0x2c51b24b,0xb3863164,0x33b430f1,0xaecc33fe,0x2fd833f1,0x333e21e3,0xb2f927a4,0x3386b164,0xb3b4b0f1,0xad70b1e9,0x2c51b24b,
0xb156a311,0x30e2a81d,0xb1f633fd,0x325633ef,0xb1f633fd,0x325633ef,0x31562311,0xb0e2281d,0x31562311,0xb0e2281d,0x31f6b3fd,0xb256b3ef,0x31f6b3fd,0xb256b3ef,0xb156a311,0x30e2a81d,
0x2d29241f,0xac082867,0x3393b3fc,0xb3beb3ed,0x332eb148,0xb2e6b0d3,0x2f10b202,0xb00db262,0x3393b3fc,0xb3beb3ed,0xad29a41f,0x2c08a867,0x2f10b202,0xb00db262,0xb32e3148,0x32e630d3,
0x98b60000,0x34003400,0xa54ca4b5,0x33f933fa,0x9f119cb6,0x33ff3400,0xa678a5e2,0x33f633f7,0xa1e3a0b6,0x33fe33ff,0xa7a4a70e,0x33f133f4,0xa41fa311,0x33fc33fd,0xa867a81d,0x33ed33ef,
0xae420000,0x335d3400,0x2f5324b5,0xb31db3fa,0xb379b1c3,0x2db6318d,0x33aa3227,0xac99b11d,0xb33eb3ff,0xaecca0b6,0x32f933f4,0x2fd8270e,0xad29b156,0xb393b1f6,0x2c0830e2,0x33be3256,
0xb1b50000,0x319b3400,0xb21ba4b5,0x312b33fa,0xb180b400,0xb1d09cb6,0xb10eb3f7,0xb233a5e2,0x31e920b6,0xb164b3ff,0x324b270e,0xb0f1b3f4,0x314833fd,0x32022311,0x30d333ef,0x3262281d,
0xb36b0000,0x2dfd3400,0x339e24b5,0xace1b3fa,0x2e87b18d,0xb34eb1c3,0xaf96311d,0x330b3227,0x2d7033ff,0x338620b6,0xac51b3f4,0xb3b4a70e,0xb32eb1f6,0xaf103156,0x32e63256,0x300db0e2,
0xb4000000,0x98b63400,0xb3f9a4b5,0xa54c33fa,0x33ff1cb6,0x1f11b400,0x33f625e2,0x2678b3f7,0xb3fea0b6,0xa1e333ff,0xb3f1a70e,0xa7a433f4,0x33fc2311,0x241fb3fd,0x33ed281d,0x2867b3ef,
0xb35d0000,0xae423400,0x331d24b5,0x2f53b3fa,0x2db631c3,0x3379b18d,0xac99b227,0xb3aa311d,0x2eccb3ff,0xb33ea0b6,0xafd833f4,0x32f9270e,0xb3933156,0x2d2931f6,0x33beb0e2,0xac08b256,
0xb19b0000,0xb1b53400,0xb12ba4b5,0xb21b33fa,0xb1d03400,0x31801cb6,0xb23333f7,0x310e25e2,0x316420b6,0x31e9b3ff,0x30f1270e,0x324bb3f4,0x3202b3fd,0xb148a311,0x3262b3ef,0xb0d3a81d,
0xadfd0000,0xb36b3400,0x2ce124b5,0x339eb3fa,0xb34e318d,0xae8731c3,0x330bb11d,0x2f96b227,0xb38633ff,0x2d7020b6,0x33b4b3f4,0xac51a70e,0xaf1031f6,0x332eb156,0x300db256,0xb2e630e2,
0x18b60000,0xb4003400,0x254ca4b5,0xb3f933fa,0x1f119cb6,0xb3ff3400,0x2678a5e2,0xb3f633f7,0x21e3a0b6,0xb3fe33ff,0x27a4a70e,0xb3f133f4,0x241fa311,0xb3fc33fd,0x2867a81d,0xb3ed33ef,
0x2e420000,0xb35d3400,0xaf5324b5,0x331db3fa,0x3379b1c3,0xadb6318d,0xb3aa3227,0x2c99b11d,0x333eb3ff,0x2ecca0b6,0xb2f933f4,0xafd8270e,0x2d29b156,0x3393b1f6,0xac0830e2,0xb3be3256,
0x31b50000,0xb19b3400,0x321ba4b5,0xb12b33fa,0x3180b400,0x31d09cb6,0x310eb3f7,0x3233a5e2,0xb1e920b6,0x3164b3ff,0xb24b270e,0x30f1b3f4,0xb14833fd,0xb2022311,0xb0d333ef,0xb262281d,
0x336b0000,0xadfd3400,0xb39e24b5,0x2ce1b3fa,0xae87b18d,0x334eb1c3,0x2f96311d,0xb30b3227,0xad7033ff,0xb38620b6,0x2c51b3f4,0x33b4a70e,0x332eb1f6,0x2f103156,0xb2e63256,0xb00db0e2,
0x34000000,0x18b63400,0x33f9a4b5,0x254c33fa,0xb3ff1cb6,0x9f11b400,0xb3f625e2,0xa678b3f7,0x33fea0b6,0x21e333ff,0x33f1a70e,0x27a433f4,0xb3fc2311,0xa41fb3fd,0xb3ed281d,0xa867b3ef,
0x335d0000,0x2e423400,0xb31d24b5,0xaf53b3fa,0xadb631c3,0xb379b18d,0x2c99b227,0x33aa311d,0xaeccb3ff,0x333ea0b6,0x2fd833f4,0xb2f9270e,0x33933156,0xad2931f6,0xb3beb0e2,0x2c08b256,
0x319b0000,0x31b53400,0x312ba4b5,0x321b33fa,0x31d03400,0xb1801cb6,0x323333f7,0xb10e25e2,0xb16420b6,0xb1e9b3ff,0xb0f1270e,0xb24bb3f4,0xb202b3fd,0x3148a311,0xb262b3ef,0x30d3a81d,
0x2dfd0000,0x336b3400,0xace124b5,0xb39eb3fa,0x334e318d,0x2e8731c3,0xb30bb11d,0xaf96b227,0x338633ff,0xad7020b6,0xb3b4b3f4,0x2c51a70e,0x2f1031f6,0xb32eb156,0xb00db256,0x32e630e2,
0x0,0x34003400,0xacb20000,0x37ea3800,0x0,0x34003400,0xb2d7b0a5,0x373b37a8,0x0,0x34003400,0xb55fb472,0x35ed36a7,0x0,0x34003400,0xb6ddb62f,0x341d3513,
0xb26da8b2,0x30c433ea,0xb66d0000,0x34c43800,0xb0c4b3ea,0xb26da8b2,0xb164b7a8,0xb788b0a5,0x326d28b2,0xb0c4b3ea,0x37fe3472,0xa648b6a7,0x30c433ea,0x326d28b2,0xafc63513,0x37c3362f,
0xb3a8aca5,0xaca533a8,0xb7ea0000,0xacb23800,0x33a82ca5,0x2ca5b3a8,0x373b30a5,0x32d7b7a8,0xb3a8aca5,0xaca533a8,0xb5edb472,0xb55f36a7,0x33a82ca5,0x2ca5b3a8,0x341d362f,0x36ddb513,
0xad64aed7,0xb388333b,0xb4c40000,0xb66d3800,0xb388333b,0x2d642ed7,0xb78837a8,0x316430a5,0x2d642ed7,0x3388b33b,0x26483472,0x37feb6a7,0x3388b33b,0xad64aed7,0x37c3b513,0x2fc6b62f,
0x3072b072,0xb2a732a7,0x2cb20000,0xb7ea3800,0x3072b072,0xb2a732a7,0x32d7b0a5,0xb73b37a8,0x3072b072,0xb2a732a7,0x355fb472,0xb5ed36a7,0x3072b072,0xb2a732a7,0x36ddb62f,0xb41d3513,
0x33feb15f,0xa24831ed,0x366d0000,0xb4c43800,0x2248b1ed,0x33feb15f,0x3164b7a8,0x3788b0a5,0xb3fe315f,0x2248b1ed,0xb7fe3472,0x2648b6a7,0xa24831ed,0xb3fe315f,0x2fc63513,0xb7c3362f,
0x3113b22f,0x322f3113,0x37ea0000,0x2cb23800,0xb113322f,0xb22fb113,0xb73b30a5,0xb2d7b7a8,0x3113b22f,0x322f3113,0x35edb472,0x355f36a7,0xb113322f,0xb22fb113,0xb41d362f,0xb6ddb513,
0xabc6b2dd,0x33c3301d,0x34c40000,0x366d3800,0x33c3301d,0x2bc632dd,0x378837a8,0xb16430a5,0x2bc632dd,0xb3c3b01d,0xa6483472,0xb7feb6a7,0xb3c3b01d,0xabc6b2dd,0xb7c3b513,0xafc6b62f,
0x0,0x2646a646,0x34003400,0xb3f633f6,0x0,0x2646a646,0x34003400,0xb3f633f6,0x0,0x2646a646,0x34003400,0xb3f633f6,0x0,0x2646a646,0x34003400,0xb3f633f6,
0xae4e9a48,0x2fb7a70e,0x335a3400,0xb30233f4,0xb36eb1ba,0x33afb23f,0x2df13196,0xac753100,0xb35ab400,0x3302b3f4,0xae4e9a48,0x2fb7a70e,0xadf1b196,0x2c75b100,0xb36eb1ba,0x33afb23f,
0xb1cb9e48,0x324fa7d6,0x318433ff,0xb0ec33f1,0xb184b3ff,0x30ecb3f1,0xb1cb9e48,0x324fa7d6,0x31cb1e48,0xb24f27d6,0xb184b3ff,0x30ecb3f1,0x318433ff,0xb0ec33f1,0x31cb1e48,0xb24f27d6,
0xb380a0b6,0x33bca84e,0x2d9333ff,0xac1433ed,0x2eaab172,0xb007b0d8,0xb346b1dc,0x32e9b25e,0x2d9333ff,0xac1433ed,0x338020b6,0xb3bc284e,0xb346b1dc,0x32e9b25e,0xaeaa3172,0x300730d8,
0xb3fea248,0x33eaa8b2,0xa24833fe,0x28b233ea,0x33fe2248,0xb3ea28b2,0x2248b3fe,0xa8b2b3ea,0xb3fea248,0x33eaa8b2,0xa24833fe,0x28b233ea,0x33fe2248,0xb3ea28b2,0x2248b3fe,0xa8b2b3ea,
0xb330a3d9,0x32d0a915,0xaf0533fc,0x303233e6,0x2d3431fe,0xab65327c,0x3391b14d,0xb3c9b0b0,0x2f05b3fc,0xb032b3e6,0xb330a3d9,0x32d0a915,0xb391314d,0x33c930b0,0x2d3431fe,0xab65327c,
0xb13aa4b5,0x309ba979,0xb20f33fa,0x328a33e2,0xb20f33fa,0x328a33e2,0x313a24b5,0xb09b2979,0x313a24b5,0xb09b2979,0x320fb3fa,0xb28ab3e2,0x320fb3fa,0xb28ab3e2,0xb13aa4b5,0x309ba979,
0xacd5a57e,0x2aa1a9db,0xb3a033f8,0x33d433dd,0xb31a3127,0x32b53087,0xaf5e321f,0x305d3299,0xb3a033f8,0x33d433dd,0x2cd5257e,0xaaa129db,0xaf5e321f,0x305d3299,0x331ab127,0xb2b5b087,
0x0,0x2646a646,0x34003400,0xb3f633f6,0x0,0x2646a646,0x34003400,0xb3f633f6,0x0,0x2646a646,0x34003400,0xb3f633f6,0x0,0x2646a646,0x34003400,0xb3f633f6,
0x2e4e1a48,0xafb7270e,0xb35ab400,0x3302b3f4,0x336e31ba,0xb3af323f,0xadf1b196,0x2c75b100,0x335a3400,0xb30233f4,0x2e4e1a48,0xafb7270e,0x2df13196,0xac753100,0x336e31ba,0xb3af323f,
0xb1cb9e48,0x324fa7d6,0x318433ff,0xb0ec33f1,0xb184b3ff,0x30ecb3f1,0xb1cb9e48,0x324fa7d6,0x31cb1e48,0xb24f27d6,0xb184b3ff,0x30ecb3f1,0x318433ff,0xb0ec33f1,0x31cb1e48,0xb24f27d6,
0x338020b6,0xb3bc284e,0xad93b3ff,0x2c14b3ed,0xaeaa3172,0x300730d8,0x334631dc,0xb2e9325e,0xad93b3ff,0x2c14b3ed,0xb380a0b6,0x33bca84e,0x334631dc,0xb2e9325e,0x2eaab172,0xb007b0d8,
0xb3fea248,0x33eaa8b2,0xa24833fe,0x28b233ea,0x33fe2248,0xb3ea28b2,0x2248b3fe,0xa8b2b3ea,0xb3fea248,0x33eaa8b2,0xa24833fe,0x28b233ea,0x33fe2248,0xb3ea28b2,0x2248b3fe,0xa8b2b3ea,
0x333023d9,0xb2d02915,0x2f05b3fc,0xb032b3e6,0xad34b1fe,0x2b65b27c,0xb391314d,0x33c930b0,0xaf0533fc,0x303233e6,0x333023d9,0xb2d02915,0x3391b14d,0xb3c9b0b0,0xad34b1fe,0x2b65b27c,
0xb13aa4b5,0x309ba979,0xb20f33fa,0x328a33e2,0xb20f33fa,0x328a33e2,0x313a24b5,0xb09b2979,0x313a24b5,0xb09b2979,0x320fb3fa,0xb28ab3e2,0x320fb3fa,0xb28ab3e2,0xb13aa4b5,0x309ba979,
0x2cd5257e,0xaaa129db,0x33a0b3f8,0xb3d4b3dd,0x331ab127,0xb2b5b087,0x2f5eb21f,0xb05db299,0x33a0b3f8,0xb3d4b3dd,0xacd5a57e,0x2aa1a9db,0x2f5eb21f,0xb05db299,0xb31a3127,0x32b53087,
0x9a480000,0x34003400,0xa70ea646,0x33f433f6,0xa0b69e48,0x33ff33ff,0xa84ea7d6,0x33ed33f1,0xa3d9a248,0x33fc33fe,0xa915a8b2,0x33e633ea,0xa57ea4b5,0x33f833fa,0xa9dba979,0x33dd33e2,
0xae4e0000,0x335a3400,0x2fb72646,0xb302b3f6,0xb380b1cb,0x2d933184,0x33bc324f,0xac14b0ec,0xb330b3fe,0xaf05a248,0x32d033ea,0x303228b2,0xacd5b13a,0xb3a0b20f,0x2aa1309b,0x33d4328a,
0xb1ba0000,0x31963400,0xb23fa646,0x310033f6,0xb172b3ff,0xb1dc9e48,0xb0d8b3f1,0xb25ea7d6,0x31fe2248,0xb14db3fe,0x327c28b2,0xb0b0b3ea,0x312733fa,0x321f24b5,0x308733e2,0x32992979,
0xb36e0000,0x2df13400,0x33af2646,0xac75b3f6,0x2eaab184,0xb346b1cb,0xb00730ec,0x32e9324f,0x2d3433fe,0x33912248,0xab65b3ea,0xb3c9a8b2,0xb31ab20f,0xaf5e313a,0x32b5328a,0x305db09b,
0xb4000000,0x9a483400,0xb3f4a646,0xa70e33f6,0x33ff1e48,0x20b6b3ff,0x33ed27d6,0x284eb3f1,0xb3fca248,0xa3d933fe,0xb3e6a8b2,0xa91533ea,0x33f824b5,0x257eb3fa,0x33dd2979,0x29dbb3e2,
0xb35a0000,0xae4e3400,0x33022646,0x2fb7b3f6,0x2d9331cb,0x3380b184,0xac14b24f,0xb3bc30ec,0x2f05b3fe,0xb330a248,0xb03233ea,0x32d028b2,0xb3a0313a,0x2cd5320f,0x33d4b09b,0xaaa1b28a,
0xb1960000,0xb1ba3400,0xb100a646,0xb23f33f6,0xb1dc33ff,0x31721e48,0xb25e33f1,0x30d827d6,0x314d2248,0x31feb3fe,0x30b028b2,0x327cb3ea,0x321fb3fa,0xb127a4b5,0x3299b3e2,0xb087a979,
0xadf10000,0xb36e3400,0x2c752646,0x33afb3f6,0xb3463184,0xaeaa31cb,0x32e9b0ec,0x3007b24f,0xb39133fe,0x2d342248,0x33c9b3ea,0xab65a8b2,0xaf5e320f,0x331ab13a,0x305db28a,0xb2b5309b,
0x1a480000,0xb4003400,0x270ea646,0xb3f433f6,0x20b69e48,0xb3ff33ff,0x284ea7d6,0xb3ed33f1,0x23d9a248,0xb3fc33fe,0x2915a8b2,0xb3e633ea,0x257ea4b5,0xb3f833fa,0x29dba979,0xb3dd33e2,
0x2e4e0000,0xb35a3400,0xafb72646,0x3302b3f6,0x3380b1cb,0xad933184,0xb3bc324f,0x2c14b0ec,0x3330b3fe,0x2f05a248,0xb2d033ea,0xb03228b2,0x2cd5b13a,0x33a0b20f,0xaaa1309b,0xb3d4328a,
0x31ba0000,0xb1963400,0x323fa646,0xb10033f6,0x3172b3ff,0x31dc9e48,0x30d8b3f1,0x325ea7d6,0xb1fe2248,0x314db3fe,0xb27c28b2,0x30b0b3ea,0xb12733fa,0xb21f24b5,0xb08733e2,0xb2992979,
0x336e0000,0xadf13400,0xb3af2646,0x2c75b3f6,0xaeaab184,0x3346b1cb,0x300730ec,0xb2e9324f,0xad3433fe,0xb3912248,0x2b65b3ea,0x33c9a8b2,0x331ab20f,0x2f5e313a,0xb2b5328a,0xb05db09b,
0x34000000,0x1a483400,0x33f4a646,0x270e33f6,0xb3ff1e48,0xa0b6b3ff,0xb3ed27d6,0xa84eb3f1,0x33fca248,0x23d933fe,0x33e6a8b2,0x291533ea,0xb3f824b5,0xa57eb3fa,0xb3dd2979,0xa9dbb3e2,
0x335a0000,0x2e4e3400,0xb3022646,0xafb7b3f6,0xad9331cb,0xb380b184,0x2c14b24f,0x33bc30ec,0xaf05b3fe,0x3330a248,0x303233ea,0xb2d028b2,0x33a0313a,0xacd5320f,0xb3d4b09b,0x2aa1b28a,
0x31960000,0x31ba3400,0x3100a646,0x323f33f6,0x31dc33ff,0xb1721e48,0x325e33f1,0xb0d827d6,0xb14d2248,0xb1feb3fe,0xb0b028b2,0xb27cb3ea,0xb21fb3fa,0x3127a4b5,0xb299b3e2,0x3087a979,
0x2df10000,0x336e3400,0xac752646,0xb3afb3f6,0x33463184,0x2eaa31cb,0xb2e9b0ec,0xb007b24f,0x339133fe,0xad342248,0xb3c9b3ea,0x2b65a8b2,0x2f5e320f,0xb31ab13a,0xb05db28a,0x32b5309b,
0x0,0x34003400,0xae3e0000,0x37d93800,0x0,0x34003400,0xb472b21f,0x36a73764,0x0,0x34003400,0xb6a7b5a8,0x347235a8,0x0,0x34003400,0xb7d9b764,0x2e3e321f,
0xb2a7aa3e,0x307233d9,0xb6a70000,0x34723800,0xb072b3d9,0xb2a7aa3e,0xae3eb764,0xb7d9b21f,0x32a72a3e,0xb072b3d9,0x37d935a8,0x2e3eb5a8,0x307233d9,0x32a72a3e,0xb472321f,0x36a73764,
0xb364ae1f,0xae1f3364,0xb7d90000,0xae3e3800,0x33642e1f,0x2e1fb364,0x36a7321f,0x3472b764,0xb364ae1f,0xae1f3364,0xb472b5a8,0xb6a735a8,0x33642e1f,0x2e1fb364,0x2e3e3764,0x37d9b21f,
0xaa3eb072,0xb3d932a7,0xb4720000,0xb6a73800,0xb3d932a7,0x2a3e3072,0xb7d93764,0x2e3e321f,0x2a3e3072,0x33d9b2a7,0xae3e35a8,0x37d9b5a8,0x33d9b2a7,0xaa3eb072,0x36a7b21f,0x3472b764,
0x31a8b1a8,0xb1a831a8,0x2e3e0000,0xb7d93800,0x31a8b1a8,0xb1a831a8,0x3472b21f,0xb6a73764,0x31a8b1a8,0xb1a831a8,0x36a7b5a8,0xb47235a8,0x31a8b1a8,0xb1a831a8,0x37d9b764,0xae3e321f,
0x33d9b2a7,0x2a3e3072,0x36a70000,0xb4723800,0xaa3eb072,0x33d9b2a7,0x2e3eb764,0x37d9b21f,0xb3d932a7,0xaa3eb072,0xb7d935a8,0xae3eb5a8,0x2a3e3072,0xb3d932a7,0x3472321f,0xb6a73764,
0x2e1fb364,0x33642e1f,0x37d90000,0x2e3e3800,0xae1f3364,0xb364ae1f,0xb6a7321f,0xb472b764,0x2e1fb364,0x33642e1f,0x3472b5a8,0x36a735a8,0xae1f3364,0xb364ae1f,0xae3e3764,0xb7d9b21f,
0xb072b3d9,0x32a72a3e,0x34720000,0x36a73800,0x32a72a3e,0x307233d9,0x37d93764,0xae3e321f,0x307233d9,0xb2a7aa3e,0x2e3e35a8,0xb7d9b5a8,0xb2a7aa3e,0xb072b3d9,0xb6a7b21f,0xb472b764,
0x0,0x27d6a7d6,0x34003400,0xb3f133f1,0x0,0x27d6a7d6,0x34003400,0xb3f133f1,0x0,0x27d6a7d6,0x34003400,0xb3f133f1,0x0,0x27d6a7d6,0x34003400,0xb3f133f1,
0xae599bdb,0x300da867,0x33583400,0xb2e633ed,0xb370b1be,0x33beb262,0x2de53192,0xac0830d3,0xb358b400,0x32e6b3ed,0xae599bdb,0x300da867,0xade5b192,0x2c08b0d3,0xb370b1be,0x33beb262,
0xb1d49fda,0x3274a8e4,0x317b33ff,0xb0ba33e8,0xb17bb3ff,0x30bab3e8,0xb1d49fda,0x3274a8e4,0x31d41fda,0xb27428e4,0xb17bb3ff,0x30bab3e8,0x317b33ff,0xb0ba33e8,0x31d41fda,0xb27428e4,
0xb386a1e3,0x33cda960,0x2d7033fe,0xab1b33e3,0x2eccb164,0xb042b0a0,0xb33eb1e9,0x32c6b287,0x2d7033fe,0xab1b33e3,0x338621e3,0xb3cd2960,0xb33eb1e9,0x32c6b287,0xaecc3164,0x304230a0,
0xb3fca3d9,0x33dda9db,0xa3d933fc,0x29db33dd,0x33fc23d9,0xb3dd29db,0x23d9b3fc,0xa9dbb3dd,0xb3fca3d9,0x33dda9db,0xa3d933fc,0x29db33dd,0x33fc23d9,0xb3dd29db,0x23d9b3fc,0xa9dbb3dd,
0xb322a4e7,0x32a3aa57,0xaf3d33fa,0x307733d7,0x2cf93213,0xaa2632aa,0x339bb135,0xb3dab06d,0x2f3db3fa,0xb077b3d7,0xb322a4e7,0x32a3aa57,0xb39b3135,0x33da306d,0x2cf93213,0xaa2632aa,
0xb11da5e2,0x3052aad2,0xb22733f7,0x32bc33d1,0xb22733f7,0x32bc33d1,0x311d25e2,0xb0522ad2,0x311d25e2,0xb0522ad2,0x3227b3f7,0xb2bcb3d1,0x3227b3f7,0xb2bcb3d1,0xb11da5e2,0x3052aad2,
0xac81a6dc,0x292eab4c,0xb3ad33f4,0x33e533ca,0xb3053105,0x327f3038,0xafac323b,0x30ab32cc,0xb3ad33f4,0x33e533ca,0x2c8126dc,0xa92e2b4c,0xafac323b,0x30ab32cc,0x3305b105,0xb27fb038,
0x0,0x27d6a7d6,0x34003400,0xb3f133f1,0x0,0x27d6a7d6,0x34003400,0xb3f133f1,0x0,0x27d6a7d6,0x34003400,0xb3f133f1,0x0,0x27d6a7d6,0x34003400,0xb3f133f1,
0x2e591bdb,0xb00d2867,0xb358b400,0x32e6b3ed,0x337031be,0xb3be3262,0xade5b192,0x2c08b0d3,0x33583400,0xb2e633ed,0x2e591bdb,0xb00d2867,0x2de53192,0xac0830d3,0x337031be,0xb3be3262,
0xb1d49fda,0x3274a8e4,0x317b33ff,0xb0ba33e8,0xb17bb3ff,0x30bab3e8,0xb1d49fda,0x3274a8e4,0x31d41fda,0xb27428e4,0xb17bb3ff,0x30bab3e8,0x317b33ff,0xb0ba33e8,0x31d41fda,0xb27428e4,
0x338621e3,0xb3cd2960,0xad70b3fe,0x2b1bb3e3,0xaecc3164,0x304230a0,0x333e31e9,0xb2c63287,0xad70b3fe,0x2b1bb3e3,0xb386a1e3,0x33cda960,0x333e31e9,0xb2c63287,0x2eccb164,0xb042b0a0,
0xb3fca3d9,0x33dda9db,0xa3d933fc,0x29db33dd,0x33fc23d9,0xb3dd29db,0x23d9b3fc,0xa9dbb3dd,0xb3fca3d9,0x33dda9db,0xa3d933fc,0x29db33dd,0x33fc23d9,0xb3dd29db,0x23d9b3fc,0xa9dbb3dd,
0x332224e7,0xb2a32a57,0x2f3db3fa,0xb077b3d7,0xacf9b213,0x2a26b2aa,0xb39b3135,0x33da306d,0xaf3d33fa,0x307733d7,0x332224e7,0xb2a32a57,0x339bb135,0xb3dab06d,0xacf9b213,0x2a26b2aa,
0xb11da5e2,0x3052aad2,0xb22733f7,0x32bc33d1,0xb22733f7,0x32bc33d1,0x311d25e2,0xb0522ad2,0x311d25e2,0xb0522ad2,0x3227b3f7,0xb2bcb3d1,0x3227b3f7,0xb2bcb3d1,0xb11da5e2,0x3052aad2,
0x2c8126dc,0xa92e2b4c,0x33adb3f4,0xb3e5b3ca,0x3305b105,0xb27fb038,0x2facb23b,0xb0abb2cc,0x33adb3f4,0xb3e5b3ca,0xac81a6dc,0x292eab4c,0x2facb23b,0xb0abb2cc,0xb3053105,0x327f3038,
0x9bdb0000,0x34003400,0xa867a7d6,0x33ed33f1,0xa1e39fda,0x33fe33ff,0xa960a8e4,0x33e333e8,0xa4e7a3d9,0x33fa33fc,0xaa57a9db,0x33d733dd,0xa6dca5e2,0x33f433f7,0xab4caad2,0x33ca33d1,
0xae590000,0x33583400,0x300d27d6,0xb2e6b3f1,0xb386b1d4,0x2d70317b,0x33cd3274,0xab1bb0ba,0xb322b3fc,0xaf3da3d9,0x32a333dd,0x307729db,0xac81b11d,0xb3adb227,0x292e3052,0x33e532bc,
0xb1be0000,0x31923400,0xb262a7d6,0x30d333f1,0xb164b3ff,0xb1e99fda,0xb0a0b3e8,0xb287a8e4,0x321323d9,0xb135b3fc,0x32aa29db,0xb06db3dd,0x310533f7,0x323b25e2,0x303833d1,0x32cc2ad2,
0xb3700000,0x2de53400,0x33be27d6,0xac08b3f1,0x2eccb17b,0xb33eb1d4,0xb04230ba,0x32c63274,0x2cf933fc,0x339b23d9,0xaa26b3dd,0xb3daa9db,0xb305b227,0xafac311d,0x327f32bc,0x30abb052,
0xb4000000,0x9bdb3400,0xb3eda7d6,0xa86733f1,0x33fe1fda,0x21e3b3ff,0x33e328e4,0x2960b3e8,0xb3faa3d9,0xa4e733fc,0xb3d7a9db,0xaa5733dd,0x33f425e2,0x26dcb3f7,0x33ca2ad2,0x2b4cb3d1,
0xb3580000,0xae593400,0x32e627d6,0x300db3f1,0x2d7031d4,0x3386b17b,0xab1bb274,0xb3cd30ba,0x2f3db3fc,0xb322a3d9,0xb07733dd,0x32a329db,0xb3ad311d,0x2c813227,0x33e5b052,0xa92eb2bc,
0xb1920000,0xb1be3400,0xb0d3a7d6,0xb26233f1,0xb1e933ff,0x31641fda,0xb28733e8,0x30a028e4,0x313523d9,0x3213b3fc,0x306d29db,0x32aab3dd,0x323bb3f7,0xb105a5e2,0x32ccb3d1,0xb038aad2,
0xade50000,0xb3703400,0x2c0827d6,0x33beb3f1,0xb33e317b,0xaecc31d4,0x32c6b0ba,0x3042b274,0xb39b33fc,0x2cf923d9,0x33dab3dd,0xaa26a9db,0xafac3227,0x3305b11d,0x30abb2bc,0xb27f3052,
0x1bdb0000,0xb4003400,0x2867a7d6,0xb3ed33f1,0x21e39fda,0xb3fe33ff,0x2960a8e4,0xb3e333e8,0x24e7a3d9,0xb3fa33fc,0x2a57a9db,0xb3d733dd,0x26dca5e2,0xb3f433f7,0x2b4caad2,0xb3ca33d1,
0x2e590000,0xb3583400,0xb00d27d6,0x32e6b3f1,0x3386b1d4,0xad70317b,0xb3cd3274,0x2b1bb0ba,0x3322b3fc,0x2f3da3d9,0xb2a333dd,0xb07729db,0x2c81b11d,0x33adb227,0xa92e3052,0xb3e532bc,
0x31be0000,0xb1923400,0x3262a7d6,0xb0d333f1,0x3164b3ff,0x31e99fda,0x30a0b3e8,0x3287a8e4,0xb21323d9,0x3135b3fc,0xb2aa29db,0x306db3dd,0xb10533f7,0xb23b25e2,0xb03833d1,0xb2cc2ad2,
0x33700000,0xade53400,0xb3be27d6,0x2c08b3f1,0xaeccb17b,0x333eb1d4,0x304230ba,0xb2c63274,0xacf933fc,0xb39b23d9,0x2a26b3dd,0x33daa9db,0x3305b227,0x2fac311d,0xb27f32bc,0xb0abb052,
0x34000000,0x1bdb3400,0x33eda7d6,0x286733f1,0xb3fe1fda,0xa1e3b3ff,0xb3e328e4,0xa960b3e8,0x33faa3d9,0x24e733fc,0x33d7a9db,0x2a5733dd,0xb3f425e2,0xa6dcb3f7,0xb3ca2ad2,0xab4cb3d1,
0x33580000,0x2e593400,0xb2e627d6,0xb00db3f1,0xad7031d4,0xb386b17b,0x2b1bb274,0x33cd30ba,0xaf3db3fc,0x3322a3d9,0x307733dd,0xb2a329db,0x33ad311d,0xac813227,0xb3e5b052,0x292eb2bc,
0x31920000,0x31be3400,0x30d3a7d6,0x326233f1,0x31e933ff,0xb1641fda,0x328733e8,0xb0a028e4,0xb13523d9,0xb213b3fc,0xb06d29db,0xb2aab3dd,0xb23bb3f7,0x3105a5e2,0xb2ccb3d1,0x3038aad2,
0x2de50000,0x33703400,0xac0827d6,0xb3beb3f1,0x333e317b,0x2ecc31d4,0xb2c6b0ba,0xb042b274,0x339b33fc,0xacf923d9,0xb3dab3dd,0x2a26a9db,0x2fac3227,0xb305b11d,0xb0abb2bc,0x327f3052,
0x0,0x34003400,0xafc60000,0x37c33800,0x0,0x34003400,0xb55fb38b,0x35ed370e,0x0,0x34003400,0xb788b6a7,0x31643472,0x0,0x34003400,0xb7eab7f6,0xacb22a46,
0xb2ddabc6,0x301d33c3,0xb6dd0000,0x341d3800,0xb01db3c3,0xb2ddabc6,0xa648b70e,0xb7feb38b,0x32dd2bc6,0xb01db3c3,0x373b36a7,0x32d7b472,0x301d33c3,0x32dd2bc6,0xb66d2a46,0x34c437f6,
0xb30eaf8b,0xaf8b330e,0xb7c30000,0xafc63800,0x330e2f8b,0x2f8bb30e,0x35ed338b,0x355fb70e,0xb30eaf8b,0xaf8b330e,0xb164b6a7,0xb7883472,0x330e2f8b,0x2f8bb30e,0xacb237f6,0x37eaaa46,
0xa248b15f,0xb3fe31ed,0xb41d0000,0xb6dd3800,0xb3fe31ed,0x2248315f,0xb7fe370e,0x2648338b,0x2248315f,0x33feb1ed,0xb2d736a7,0x373bb472,0x33feb1ed,0xa248b15f,0x34c4aa46,0x366db7f6,
0x32a7b2a7,0xb0723072,0x2fc60000,0xb7c33800,0x32a7b2a7,0xb0723072,0x355fb38b,0xb5ed370e,0x32a7b2a7,0xb0723072,0x3788b6a7,0xb1643472,0x32a7b2a7,0xb0723072,0x37eab7f6,0x2cb22a46,
0x333bb388,0x2ed72d64,0x36dd0000,0xb41d3800,0xaed7ad64,0x333bb388,0x2648b70e,0x37feb38b,0xb33b3388,0xaed7ad64,0xb73b36a7,0xb2d7b472,0x2ed72d64,0xb33b3388,0x366d2a46,0xb4c437f6,
0x2646b3f6,0x33f62646,0x37c30000,0x2fc63800,0xa64633f6,0xb3f6a646,0xb5ed338b,0xb55fb70e,0x2646b3f6,0x33f62646,0x3164b6a7,0x37883472,0xa64633f6,0xb3f6a646,0x2cb237f6,0xb7eaaa46,
0xb26db3ea,0x30c4a8b2,0x341d0000,0x36dd3800,0x30c4a8b2,0x326d33ea,0x37fe370e,0xa648338b,0x326d33ea,0xb0c428b2,0x32d736a7,0xb73bb472,0xb0c428b2,0xb26db3ea,0xb4c4aa46,0xb66db7f6,
0x0,0x28b2a8b2,0x34003400,0xb3ea33ea,0x0,0x28b2a8b2,0x34003400,0xb3ea33ea,0x0,0x28b2a8b2,0x34003400,0xb3ea33ea,0x0,0x28b2a8b2,0x34003400,0xb3ea33ea,
0xae659cb6,0x303da947,0x33553400,0xb2c933e4,0xb372b1c3,0x33cbb283,0x2dda318d,0xab3430a6,0xb355b400,0x32c9b3e4,0xae659cb6,0x303da947,0xaddab18d,0x2b34b0a6,0xb372b1c3,0x33cbb283,
0xb1dca0b6,0x3299a9db,0x317233ff,0xb08733dd,0xb172b3ff,0x3087b3dd,0xb1dca0b6,0x3299a9db,0x31dc20b6,0xb29929db,0xb172b3ff,0x3087b3dd,0x317233ff,0xb08733dd,0x31dc20b6,0xb29929db,
0xb38ca311,0x33dbaa6f,0x2d4c33fd,0xaa0d33d6,0x2eeeb156,0xb07cb067,0xb336b1f6,0x32a0b2ae,0x2d4c33fd,0xaa0d33d6,0x338c2311,0xb3db2a6f,0xb336b1f6,0x32a0b2ae,0xaeee3156,0x307c3067,
0xb3faa4b5,0x33ceab03,0xa4b533fa,0x2b0333ce,0x33fa24b5,0xb3ce2b03,0x24b5b3fa,0xab03b3ce,0xb3faa4b5,0x33ceab03,0xa4b533fa,0x2b0333ce,0x33fa24b5,0xb3ce2b03,0x24b5b3fa,0xab03b3ce,
0xb314a5e2,0x3274ab96,0xaf7533f7,0x30ba33c6,0x2cbd3227,0xa8e432d6,0x33a4b11d,0xb3e8b028,0x2f75b3f7,0xb0bab3c6,0xb314a5e2,0x3274ab96,0xb3a4311d,0x33e83028,0x2cbd3227,0xa8e432d6,
0xb100a70e,0x3007ac14,0xb23f33f4,0x32e933bc,0xb23f33f4,0x32e933bc,0x3100270e,0xb0072c14,0x3100270e,0xb0072c14,0x323fb3f4,0xb2e9b3bc,0x323fb3f4,0xb2e9b3bc,0xb100a70e,0x3007ac14,
0xac2ca81d,0x2772ac5d,0xb3b933ef,0x33f233b2,0xb2f030e2,0x32472fcd,0xaff93256,0x30f632fc,0xb3b933ef,0x33f233b2,0x2c2c281d,0xa7722c5d,0xaff93256,0x30f632fc,0x32f0b0e2,0xb247afcd,
0x0,0x28b2a8b2,0x34003400,0xb3ea33ea,0x0,0x28b2a8b2,0x34003400,0xb3ea33ea,0x0,0x28b2a8b2,0x34003400,0xb3ea33ea,0x0,0x28b2a8b2,0x34003400,0xb3ea33ea,
0x2e651cb6,0xb03d2947,0xb355b400,0x32c9b3e4,0x337231c3,0xb3cb3283,0xaddab18d,0x2b34b0a6,0x33553400,0xb2c933e4,0x2e651cb6,0xb03d2947,0x2dda318d,0xab3430a6,0x337231c3,0xb3cb3283,
0xb1dca0b6,0x3299a9db,0x317233ff,0xb08733dd,0xb172b3ff,0x3087b3dd,0xb1dca0b6,0x3299a9db,0x31dc20b6,0xb29929db,0xb172b3ff,0x3087b3dd,0x317233ff,0xb08733dd,0x31dc20b6,0xb29929db,
0x338c2311,0xb3db2a6f,0xad4cb3fd,0x2a0db3d6,0xaeee3156,0x307c3067,0x333631f6,0xb2a032ae,0xad4cb3fd,0x2a0db3d6,0xb38ca311,0x33dbaa6f,0x333631f6,0xb2a032ae,0x2eeeb156,0xb07cb067,
0xb3faa4b5,0x33ceab03,0xa4b533fa,0x2b0333ce,0x33fa24b5,0xb3ce2b03,0x24b5b3fa,0xab03b3ce,0xb3faa4b5,0x33ceab03,0xa4b533fa,0x2b0333ce,0x33fa24b5,0xb3ce2b03,0x24b5b3fa,0xab03b3ce,
0x331425e2,0xb2742b96,0x2f75b3f7,0xb0bab3c6,0xacbdb227,0x28e4b2d6,0xb3a4311d,0x33e83028,0xaf7533f7,0x30ba33c6,0x331425e2,0xb2742b96,0x33a4b11d,0xb3e8b028,0xacbdb227,0x28e4b2d6,
0xb100a70e,0x3007ac14,0xb23f33f4,0x32e933bc,0xb23f33f4,0x32e933bc,0x3100270e,0xb0072c14,0x3100270e,0xb0072c14,0x323fb3f4,0xb2e9b3bc,0x323fb3f4,0xb2e9b3bc,0xb100a70e,0x3007ac14,
0x2c2c281d,0xa7722c5d,0x33b9b3ef,0xb3f2b3b2,0x32f0b0e2,0xb247afcd,0x2ff9b256,0xb0f6b2fc,0x33b9b3ef,0xb3f2b3b2,0xac2ca81d,0x2772ac5d,0x2ff9b256,0xb0f6b2fc,0xb2f030e2,0x32472fcd,
0x9cb60000,0x34003400,0xa947a8b2,0x33e433ea,0xa311a0b6,0x33fd33ff,0xaa6fa9db,0x33d633dd,0xa5e2a4b5,0x33f733fa,0xab96ab03,0x33c633ce,0xa81da70e,0x33ef33f4,0xac5dac14,0x33b233bc,
0xae650000,0x33553400,0x303d28b2,0xb2c9b3ea,0xb38cb1dc,0x2d4c3172,0x33db3299,0xaa0db087,0xb314b3fa,0xaf75a4b5,0x327433ce,0x30ba2b03,0xac2cb100,0xb3b9b23f,0x27723007,0x33f232e9,
0xb1c30000,0x318d3400,0xb283a8b2,0x30a633ea,0xb156b3ff,0xb1f6a0b6,0xb067b3dd,0xb2aea9db,0x322724b5,0xb11db3fa,0x32d62b03,0xb028b3ce,0x30e233f4,0x3256270e,0x2fcd33bc,0x32fc2c14,
0xb3720000,0x2dda3400,0x33cb28b2,0xab34b3ea,0x2eeeb172,0xb336b1dc,0xb07c3087,0x32a03299,0x2cbd33fa,0x33a424b5,0xa8e4b3ce,0xb3e8ab03,0xb2f0b23f,0xaff93100,0x324732e9,0x30f6b007,
0xb4000000,0x9cb63400,0xb3e4a8b2,0xa94733ea,0x33fd20b6,0x2311b3ff,0x33d629db,0x2a6fb3dd,0xb3f7a4b5,0xa5e233fa,0xb3c6ab03,0xab9633ce,0x33ef270e,0x281db3f4,0x33b22c14,0x2c5db3bc,
0xb3550000,0xae653400,0x32c928b2,0x303db3ea,0x2d4c31dc,0x338cb172,0xaa0db299,0xb3db3087,0x2f75b3fa,0xb314a4b5,0xb0ba33ce,0x32742b03,0xb3b93100,0x2c2c323f,0x33f2b007,0xa772b2e9,
0xb18d0000,0xb1c33400,0xb0a6a8b2,0xb28333ea,0xb1f633ff,0x315620b6,0xb2ae33dd,0x306729db,0x311d24b5,0x3227b3fa,0x30282b03,0x32d6b3ce,0x3256b3f4,0xb0e2a70e,0x32fcb3bc,0xafcdac14,
0xadda0000,0xb3723400,0x2b3428b2,0x33cbb3ea,0xb3363172,0xaeee31dc,0x32a0b087,0x307cb299,0xb3a433fa,0x2cbd24b5,0x33e8b3ce,0xa8e4ab03,0xaff9323f,0x32f0b100,0x30f6b2e9,0xb2473007,
0x1cb60000,0xb4003400,0x2947a8b2,0xb3e433ea,0x2311a0b6,0xb3fd33ff,0x2a6fa9db,0xb3d633dd,0x25e2a4b5,0xb3f733fa,0x2b96ab03,0xb3c633ce,0x281da70e,0xb3ef33f4,0x2c5dac14,0xb3b233bc,
0x2e650000,0xb3553400,0xb03d28b2,0x32c9b3ea,0x338cb1dc,0xad4c3172,0xb3db3299,0x2a0db087,0x3314b3fa,0x2f75a4b5,0xb27433ce,0xb0ba2b03,0x2c2cb100,0x33b9b23f,0xa7723007,0xb3f232e9,
0x31c30000,0xb18d3400,0x3283a8b2,0xb0a633ea,0x3156b3ff,0x31f6a0b6,0x3067b3dd,0x32aea9db,0xb22724b5,0x311db3fa,0xb2d62b03,0x3028b3ce,0xb0e233f4,0xb256270e,0xafcd33bc,0xb2fc2c14,
0x33720000,0xadda3400,0xb3cb28b2,0x2b34b3ea,0xaeeeb172,0x3336b1dc,0x307c3087,0xb2a03299,0xacbd33fa,0xb3a424b5,0x28e4b3ce,0x33e8ab03,0x32f0b23f,0x2ff93100,0xb24732e9,0xb0f6b007,
0x34000000,0x1cb63400,0x33e4a8b2,0x294733ea,0xb3fd20b6,0xa311b3ff,0xb3d629db,0xaa6fb3dd,0x33f7a4b5,0x25e233fa,0x33c6ab03,0x2b9633ce,0xb3ef270e,0xa81db3f4,0xb3b22c14,0xac5db3bc,
0x33550000,0x2e653400,0xb2c928b2,0xb03db3ea,0xad4c31dc,0xb38cb172,0x2a0db299,0x33db3087,0xaf75b3fa,0x3314a4b5,0x30ba33ce,0xb2742b03,0x33b93100,0xac2c323f,0xb3f2b007,0x2772b2e9,
0x318d0000,0x31c33400,0x30a6a8b2,0x328333ea,0x31f633ff,0xb15620b6,0x32ae33dd,0xb06729db,0xb11d24b5,0xb227b3fa,0xb0282b03,0xb2d6b3ce,0xb256b3f4,0x30e2a70e,0xb2fcb3bc,0x2fcdac14,
0x2dda0000,0x33723400,0xab3428b2,0xb3cbb3ea,0x33363172,0x2eee31dc,0xb2a0b087,0xb07cb299,0x33a433fa,0xacbd24b5,0xb3e8b3ce,0x28e4ab03,0x2ff9323f,0xb2f0b100,0xb0f6b2e9,0x32473007,
0x0,0x34003400,0xb0a50000,0x37a83800,0x0,0x34003400,0xb62fb472,0x351336a7,0x0,0x34003400,0xb7f6b764,0x2a46321f,0x0,0x34003400,0xb70eb7d9,0xb38bae3e,
0xb30eaca5,0x2f8b33a8,0xb70e0000,0x338b3800,0xaf8bb3a8,0xb30eaca5,0x2a46b6a7,0xb7f6b472,0x330e2ca5,0xaf8bb3a8,0x362f3764,0x3513b21f,0x2f8b33a8,0x330e2ca5,0xb7a8ae3e,0x30a537d9,
0xb2a7b072,0xb07232a7,0xb7a80000,0xb0a53800,0x32a73072,0x3072b2a7,0x35133472,0x362fb6a7,0xb2a7b072,0xb07232a7,0xaa46b764,0xb7f6321f,0x32a73072,0x3072b2a7,0xb38b37d9,0x370e2e3e,
0x2646b22f,0xb3f63113,0xb38b0000,0xb70e3800,0xb3f63113,0xa646322f,0xb7f636a7,0xaa463472,0xa646322f,0x33f6b113,0xb5133764,0x362fb21f,0x33f6b113,0x2646b22f,0x30a52e3e,0x37a8b7d9,
0x3364b364,0xae1f2e1f,0x30a50000,0xb7a83800,0x3364b364,0xae1f2e1f,0x362fb472,0xb51336a7,0x3364b364,0xae1f2e1f,0x37f6b764,0xaa46321f,0x3364b364,0xae1f2e1f,0x370eb7d9,0x338bae3e,
0x322fb3f6,0x31132646,0x370e0000,0xb38b3800,0xb113a646,0x322fb3f6,0xaa46b6a7,0x37f6b472,0xb22f33f6,0xb113a646,0xb62f3764,0xb513b21f,0x31132646,0xb22f33f6,0x37a8ae3e,0xb0a537d9,
0xaa3eb3d9,0x33d9aa3e,0x37a80000,0x30a53800,0x2a3e33d9,0xb3d92a3e,0xb5133472,0xb62fb6a7,0xaa3eb3d9,0x33d9aa3e,0x2a46b764,0x37f6321f,0x2a3e33d9,0xb3d92a3e,0x338b37d9,0xb70e2e3e,
0xb3a8b30e,0x2ca5af8b,0x338b0000,0x370e3800,0x2ca5af8b,0x33a8330e,0x37f636a7,0x2a463472,0x33a8330e,0xaca52f8b,0x35133764,0xb62fb21f,0xaca52f8b,0xb3a8b30e,0xb0a52e3e,0xb7a8b7d9,
0x0,0x2979a979,0x34003400,0xb3e233e2,0x0,0x2979a979,0x34003400,0xb3e233e2,0x0,0x2979a979,0x34003400,0xb3e233e2,0x0,0x2979a979,0x34003400,0xb3e233e2,
0xae709d7f,0x306daa26,0x33533400,0xb2aa33da,0xb374b1c7,0x33d7b2a3,0x2dce3189,0xaa573077,0xb353b400,0x32aab3da,0xae709d7f,0x306daa26,0xadceb189,0x2a57b077,0xb374b1c7,0x33d7b2a3,
0xb1e5a17f,0x32bcaad2,0x316933fe,0xb05233d1,0xb169b3fe,0x3052b3d1,0xb1e5a17f,0x32bcaad2,0x31e5217f,0xb2bc2ad2,0xb169b3fe,0x3052b3d1,0x316933fe,0xb05233d1,0x31e5217f,0xb2bc2ad2,
0xb393a41f,0x33e7ab7d,0x2d2933fc,0xa8fd33c7,0x2f10b148,0xb0b5b02d,0xb32eb202,0x3278b2d3,0x2d2933fc,0xa8fd33c7,0x3393241f,0xb3e72b7d,0xb32eb202,0x3278b2d3,0xaf103148,0x30b5302d,
0xb3f8a57e,0x33bcac14,0xa57e33f8,0x2c1433bc,0x33f8257e,0xb3bc2c14,0x257eb3f8,0xac14b3bc,0xb3f8a57e,0x33bcac14,0xa57e33f8,0x2c1433bc,0x33f8257e,0xb3bc2c14,0x257eb3f8,0xac14b3bc,
0xb305a6dc,0x3243ac69,0xafac33f4,0x30fb33b1,0x2c81323b,0xa74032ff,0x33adb105,0xb3f3afc2,0x2facb3f4,0xb0fbb3b1,0xb305a6dc,0x3243ac69,0xb3ad3105,0x33f32fc2,0x2c81323b,0xa74032ff,
0xb0e2a81d,0x2f75acbd,0xb25633ef,0x331433a4,0xb25633ef,0x331433a4,0x30e2281d,0xaf752cbd,0x30e2281d,0xaf752cbd,0x3256b3ef,0xb314b3a4,0x3256b3ef,0xb314b3a4,0xb0e2a81d,0x2f75acbd,
0xabaea8cb,0x2483ad11,0xb3c433e9,0x33fb3397,0xb2d930bf,0x320b2f26,0xb0223271,0x313e3328,0xb3c433e9,0x33fb3397,0x2bae28cb,0xa4832d11,0xb0223271,0x313e3328,0x32d9b0bf,0xb20baf26,
0x0,0x2979a979,0x34003400,0xb3e233e2,0x0,0x2979a979,0x34003400,0xb3e233e2,0x0,0x2979a979,0x34003400,0xb3e233e2,0x0,0x2979a979,0x34003400,0xb3e233e2,
0x2e701d7f,0xb06d2a26,0xb353b400,0x32aab3da,0x337431c7,0xb3d732a3,0xadceb189,0x2a57b077,0x33533400,0xb2aa33da,0x2e701d7f,0xb06d2a26,0x2dce3189,0xaa573077,0x337431c7,0xb3d732a3,
0xb1e5a17f,0x32bcaad2,0x316933fe,0xb05233d1,0xb169b3fe,0x3052b3d1,0xb1e5a17f,0x32bcaad2,0x31e5217f,0xb2bc2ad2,0xb169b3fe,0x3052b3d1,0x316933fe,0xb05233d1,0x31e5217f,0xb2bc2ad2,
0x3393241f,0xb3e72b7d,0xad29b3fc,0x28fdb3c7,0xaf103148,0x30b5302d,0x332e3202,0xb27832d3,0xad29b3fc,0x28fdb3c7,0xb393a41f,0x33e7ab7d,0x332e3202,0xb27832d3,0x2f10b148,0xb0b5b02d,
0xb3f8a57e,0x33bcac14,0xa57e33f8,0x2c1433bc,0x33f8257e,0xb3bc2c14,0x257eb3f8,0xac14b3bc,0xb3f8a57e,0x33bcac14,0xa57e33f8,0x2c1433bc,0x33f8257e,0xb3bc2c14,0x257eb3f8,0xac14b3bc,
0x330526dc,0xb2432c69,0x2facb3f4,0xb0fbb3b1,0xac81b23b,0x2740b2ff,0xb3ad3105,0x33f32fc2,0xafac33f4,0x30fb33b1,0x330526dc,0xb2432c69,0x33adb105,0xb3f3afc2,0xac81b23b,0x2740b2ff,
0xb0e2a81d,0x2f75acbd,0xb25633ef,0x331433a4,0xb25633ef,0x331433a4,0x30e2281d,0xaf752cbd,0x30e2281d,0xaf752cbd,0x3256b3ef,0xb314b3a4,0x3256b3ef,0xb314b3a4,0xb0e2a81d,0x2f75acbd,
0x2bae28cb,0xa4832d11,0x33c4b3e9,0xb3fbb397,0x32d9b0bf,0xb20baf26,0x3022b271,0xb13eb328,0x33c4b3e9,0xb3fbb397,0xabaea8cb,0x2483ad11,0x3022b271,0xb13eb328,0xb2d930bf,0x320b2f26,
0x9d7f0000,0x34003400,0xaa26a979,0x33da33e2,0xa41fa17f,0x33fc33fe,0xab7daad2,0x33c733d1,0xa6dca57e,0x33f433f8,0xac69ac14,0x33b133bc,0xa8cba81d,0x33e933ef,0xad11acbd,0x339733a4,
0xae700000,0x33533400,0x306d2979,0xb2aab3e2,0xb393b1e5,0x2d293169,0x33e732bc,0xa8fdb052,0xb305b3f8,0xafaca57e,0x324333bc,0x30fb2c14,0xabaeb0e2,0xb3c4b256,0x24832f75,0x33fb3314,
0xb1c70000,0x31893400,0xb2a3a979,0x307733e2,0xb148b3fe,0xb202a17f,0xb02db3d1,0xb2d3aad2,0x323b257e,0xb105b3f8,0x32ff2c14,0xafc2b3bc,0x30bf33ef,0x3271281d,0x2f2633a4,0x33282cbd,
0xb3740000,0x2dce3400,0x33d72979,0xaa57b3e2,0x2f10b169,0xb32eb1e5,0xb0b53052,0x327832bc,0x2c8133f8,0x33ad257e,0xa740b3bc,0xb3f3ac14,0xb2d9b256,0xb02230e2,0x320b3314,0x313eaf75,
0xb4000000,0x9d7f3400,0xb3daa979,0xaa2633e2,0x33fc217f,0x241fb3fe,0x33c72ad2,0x2b7db3d1,0xb3f4a57e,0xa6dc33f8,0xb3b1ac14,0xac6933bc,0x33e9281d,0x28cbb3ef,0x33972cbd,0x2d11b3a4,
0xb3530000,0xae703400,0x32aa2979,0x306db3e2,0x2d2931e5,0x3393b169,0xa8fdb2bc,0xb3e73052,0x2facb3f8,0xb305a57e,0xb0fb33bc,0x32432c14,0xb3c430e2,0x2bae3256,0x33fbaf75,0xa483b314,
0xb1890000,0xb1c73400,0xb077a979,0xb2a333e2,0xb20233fe,0x3148217f,0xb2d333d1,0x302d2ad2,0x3105257e,0x323bb3f8,0x2fc22c14,0x32ffb3bc,0x3271b3ef,0xb0bfa81d,0x3328b3a4,0xaf26acbd,
0xadce0000,0xb3743400,0x2a572979,0x33d7b3e2,0xb32e3169,0xaf1031e5,0x3278b052,0x30b5b2bc,0xb3ad33f8,0x2c81257e,0x33f3b3bc,0xa740ac14,0xb0223256,0x32d9b0e2,0x313eb314,0xb20b2f75,
0x1d7f0000,0xb4003400,0x2a26a979,0xb3da33e2,0x241fa17f,0xb3fc33fe,0x2b7daad2,0xb3c733d1,0x26dca57e,0xb3f433f8,0x2c69ac14,0xb3b133bc,0x28cba81d,0xb3e933ef,0x2d11acbd,0xb39733a4,
0x2e700000,0xb3533400,0xb06d2979,0x32aab3e2,0x3393b1e5,0xad293169,0xb3e732bc,0x28fdb052,0x3305b3f8,0x2faca57e,0xb24333bc,0xb0fb2c14,0x2baeb0e2,0x33c4b256,0xa4832f75,0xb3fb3314,
0x31c70000,0xb1893400,0x32a3a979,0xb07733e2,0x3148b3fe,0x3202a17f,0x302db3d1,0x32d3aad2,0xb23b257e,0x3105b3f8,0xb2ff2c14,0x2fc2b3bc,0xb0bf33ef,0xb271281d,0xaf2633a4,0xb3282cbd,
0x33740000,0xadce3400,0xb3d72979,0x2a57b3e2,0xaf10b169,0x332eb1e5,0x30b53052,0xb27832bc,0xac8133f8,0xb3ad257e,0x2740b3bc,0x33f3ac14,0x32d9b256,0x302230e2,0xb20b3314,0xb13eaf75,
0x34000000,0x1d7f3400,0x33daa979,0x2a2633e2,0xb3fc217f,0xa41fb3fe,0xb3c72ad2,0xab7db3d1,0x33f4a57e,0x26dc33f8,0x33b1ac14,0x2c6933bc,0xb3e9281d,0xa8cbb3ef,0xb3972cbd,0xad11b3a4,
0x33530000,0x2e703400,0xb2aa2979,0xb06db3e2,0xad2931e5,0xb393b169,0x28fdb2bc,0x33e73052,0xafacb3f8,0x3305a57e,0x30fb33bc,0xb2432c14,0x33c430e2,0xabae3256,0xb3fbaf75,0x2483b314,
0x31890000,0x31c73400,0x3077a979,0x32a333e2,0x320233fe,0xb148217f,0x32d333d1,0xb02d2ad2,0xb105257e,0xb23bb3f8,0xafc22c14,0xb2ffb3bc,0xb271b3ef,0x30bfa81d,0xb328b3a4,0x2f26acbd,
0x2dce0000,0x33743400,0xaa572979,0xb3d7b3e2,0x332e3169,0x2f1031e5,0xb278b052,0xb0b5b2bc,0x33ad33f8,0xac81257e,0xb3f3b3bc,0x2740ac14,0x30223256,0xb2d9b0e2,0xb13eb314,0x320b2f75,
0x0,0x34003400,0xb1640000,0x37883800,0x0,0x34003400,0xb6ddb513,0x341d362f,0x0,0x34003400,0xb7eab7d9,0xacb22e3e,0x0,0x34003400,0xb55fb70e,0xb5edb38b,
0xb33bad64,0x2ed73388,0xb73b0000,0x32d73800,0xaed7b388,0xb33bad64,0x2fc6b62f,0xb7c3b513,0x333b2d64,0xaed7b388,0x34c437d9,0x366dae3e,0x2ed73388,0x333b2d64,0xb7feb38b,0xa648370e,
0xb22fb113,0xb113322f,0xb7880000,0xb1643800,0x322f3113,0x3113b22f,0x341d3513,0x36ddb62f,0xb22fb113,0xb113322f,0x2cb2b7d9,0xb7ea2e3e,0x322f3113,0x3113b22f,0xb5ed370e,0x355f338b,
0x2bc6b2dd,0xb3c3301d,0xb2d70000,0xb73b3800,0xb3c3301d,0xabc632dd,0xb7c3362f,0xafc63513,0xabc632dd,0x33c3b01d,0xb66d37d9,0x34c4ae3e,0x33c3b01d,0x2bc6b2dd,0xa648338b,0x37feb70e,
0x33d9b3d9,0xaa3e2a3e,0x31640000,0xb7883800,0x33d9b3d9,0xaa3e2a3e,0x36ddb513,0xb41d362f,0x33d9b3d9,0xaa3e2a3e,0x37eab7d9,0x2cb22e3e,0x33d9b3d9,0xaa3e2a3e,0x355fb70e,0x35edb38b,
0x30c4b3ea,0x326da8b2,0x373b0000,0xb2d73800,0xb26d28b2,0x30c4b3ea,0xafc6b62f,0x37c3b513,0xb0c433ea,0xb26d28b2,0xb4c437d9,0xb66dae3e,0x326da8b2,0xb0c433ea,0x37feb38b,0x2648370e,
0xaf8bb30e,0x330eaf8b,0x37880000,0x31643800,0x2f8b330e,0xb30e2f8b,0xb41d3513,0xb6ddb62f,0xaf8bb30e,0x330eaf8b,0xacb2b7d9,0x37ea2e3e,0x2f8b330e,0xb30e2f8b,0x35ed370e,0xb55f338b,
0xb3feb15f,0xa248b1ed,0x32d70000,0x373b3800,0xa248b1ed,0x33fe315f,0x37c3362f,0x2fc63513,0x33fe315f,0x224831ed,0x366d37d9,0xb4c4ae3e,0x224831ed,0xb3feb15f,0x2648338b,0xb7feb70e,
0x0,0x2a3eaa3e,0x34003400,0xb3d933d9,0x0,0x2a3eaa3e,0x34003400,0xb3d933d9,0x0,0x2a3eaa3e,0x34003400,0xb3d933d9,0x0,0x2a3eaa3e,0x34003400,0xb3d933d9,
0xae7c9e48,0x309bab03,0x335033ff,0xb28a33ce,0xb377b1cb,0x33e2b2c2,0x2dc23184,0xa9793048,0xb350b3ff,0x328ab3ce,0xae7c9e48,0x309bab03,0xadc2b184,0x2979b048,0xb377b1cb,0x33e2b2c2,
0xb1eda248,0x32ddabc6,0x315f33fe,0xb01d33c3,0xb15fb3fe,0x301db3c3,0xb1eda248,0x32ddabc6,0x31ed2248,0xb2dd2bc6,0xb15fb3fe,0x301db3c3,0x315f33fe,0xb01d33c3,0x31ed2248,0xb2dd2bc6,
0xb399a4b5,0x33f1ac44,0x2d0533fa,0xa7d633b6,0x2f32b13a,0xb0ecafe3,0xb325b20f,0x324fb2f6,0x2d0533fa,0xa7d633b6,0x339924b5,0xb3f12c44,0xb325b20f,0x324fb2f6,0xaf32313a,0x30ec2fe3,
0xb3f6a646,0x33a8aca5,0xa64633f6,0x2ca533a8,0x33f62646,0xb3a82ca5,0x2646b3f6,0xaca5b3a8,0xb3f6a646,0x33a8aca5,0xa64633f6,0x2ca533a8,0x33f62646,0xb3a82ca5,0x2646b3f6,0xaca5b3a8,
0xb2f6a7d6,0x320fad05,0xafe333f1,0x313a3399,0x2c44324f,0xa4b53325,0x33b6b0ec,0xb3faaf32,0x2fe3b3f1,0xb13ab399,0xb2f6a7d6,0x320fad05,0xb3b630ec,0x33fa2f32,0x2c44324f,0xa4b53325,
0xb0c4a8b2,0x2ed7ad64,0xb26d33ea,0x333b3388,0xb26d33ea,0x333b3388,0x30c428b2,0xaed72d64,0x30c428b2,0xaed72d64,0x326db3ea,0xb33bb388,0x326db3ea,0xb33bb388,0xb0c4a8b2,0x2ed7ad64,
0xab03a979,0x1e48adc2,0xb3ce33e2,0x33ff3377,0xb2c2309b,0x31cb2e7c,0xb048328a,0x31843350,0xb3ce33e2,0x33ff3377,0x2b032979,0x9e482dc2,0xb048328a,0x31843350,0x32c2b09b,0xb1cbae7c,
0x0,0x2a3eaa3e,0x34003400,0xb3d933d9,0x0,0x2a3eaa3e,0x34003400,0xb3d933d9,0x0,0x2a3eaa3e,0x34003400,0xb3d933d9,0x0,0x2a3eaa3e,0x34003400,0xb3d933d9,
0x2e7c1e48,0xb09b2b03,0xb350b3ff,0x328ab3ce,0x337731cb,0xb3e232c2,0xadc2b184,0x2979b048,0x335033ff,0xb28a33ce,0x2e7c1e48,0xb09b2b03,0x2dc23184,0xa9793048,0x337731cb,0xb3e232c2,
0xb1eda248,0x32ddabc6,0x315f33fe,0xb01d33c3,0xb15fb3fe,0x301db3c3,0xb1eda248,0x32ddabc6,0x31ed2248,0xb2dd2bc6,0xb15fb3fe,0x301db3c3,0x315f33fe,0xb01d33c3,0x31ed2248,0xb2dd2bc6,
0x339924b5,0xb3f12c44,0xad05b3fa,0x27d6b3b6,0xaf32313a,0x30ec2fe3,0x3325320f,0xb24f32f6,0xad05b3fa,0x27d6b3b6,0xb399a4b5,0x33f1ac44,0x3325320f,0xb24f32f6,0x2f32b13a,0xb0ecafe3,
0xb3f6a646,0x33a8aca5,0xa64633f6,0x2ca533a8,0x33f62646,0xb3a82ca5,0x2646b3f6,0xaca5b3a8,0xb3f6a646,0x33a8aca5,0xa64633f6,0x2ca533a8,0x33f62646,0xb3a82ca5,0x2646b3f6,0xaca5b3a8,
0x32f627d6,0xb20f2d05,0x2fe3b3f1,0xb13ab399,0xac44b24f,0x24b5b325,0xb3b630ec,0x33fa2f32,0xafe333f1,0x313a3399,0x32f627d6,0xb20f2d05,0x33b6b0ec,0xb3faaf32,0xac44b24f,0x24b5b325,
0xb0c4a8b2,0x2ed7ad64,0xb26d33ea,0x333b3388,0xb26d33ea,0x333b3388,0x30c428b2,0xaed72d64,0x30c428b2,0xaed72d64,0x326db3ea,0xb33bb388,0x326db3ea,0xb33bb388,0xb0c4a8b2,0x2ed7ad64,
0x2b032979,0x9e482dc2,0x33ceb3e2,0xb3ffb377,0x32c2b09b,0xb1cbae7c,0x3048b28a,0xb184b350,0x33ceb3e2,0xb3ffb377,0xab03a979,0x1e48adc2,0x3048b28a,0xb184b350,0xb2c2309b,0x31cb2e7c,
0x9e480000,0x33ff3400,0xab03aa3e,0x33ce33d9,0xa4b5a248,0x33fa33fe,0xac44abc6,0x33b633c3,0xa7d6a646,0x33f133f6,0xad05aca5,0x339933a8,0xa979a8b2,0x33e233ea,0xadc2ad64,0x33773388,
0xae7c0000,0x33503400,0x309b2a3e,0xb28ab3d9,0xb399b1ed,0x2d05315f,0x33f132dd,0xa7d6b01d,0xb2f6b3f6,0xafe3a646,0x320f33a8,0x313a2ca5,0xab03b0c4,0xb3ceb26d,0x1e482ed7,0x33ff333b,
0xb1cb0000,0x31843400,0xb2c2aa3e,0x304833d9,0xb13ab3fe,0xb20fa248,0xafe3b3c3,0xb2f6abc6,0x324f2646,0xb0ecb3f6,0x33252ca5,0xaf32b3a8,0x309b33ea,0x328a28b2,0x2e7c3388,0x33502d64,
0xb3770000,0x2dc23400,0x33e22a3e,0xa979b3d9,0x2f32b15f,0xb325b1ed,0xb0ec301d,0x324f32dd,0x2c4433f6,0x33b62646,0xa4b5b3a8,0xb3faaca5,0xb2c2b26d,0xb04830c4,0x31cb333b,0x3184aed7,
0xb3ff0000,0x9e483400,0xb3ceaa3e,0xab0333d9,0x33fa2248,0x24b5b3fe,0x33b62bc6,0x2c44b3c3,0xb3f1a646,0xa7d633f6,0xb399aca5,0xad0533a8,0x33e228b2,0x2979b3ea,0x33772d64,0x2dc2b388,
0xb3500000,0xae7c3400,0x328a2a3e,0x309bb3d9,0x2d0531ed,0x3399b15f,0xa7d6b2dd,0xb3f1301d,0x2fe3b3f6,0xb2f6a646,0xb13a33a8,0x320f2ca5,0xb3ce30c4,0x2b03326d,0x33ffaed7,0x9e48b33b,
0xb1840000,0xb1cb3400,0xb048aa3e,0xb2c233d9,0xb20f33fe,0x313a2248,0xb2f633c3,0x2fe32bc6,0x30ec2646,0x324fb3f6,0x2f322ca5,0x3325b3a8,0x328ab3ea,0xb09ba8b2,0x3350b388,0xae7cad64,
0xadc20000,0xb3773400,0x29792a3e,0x33e2b3d9,0xb325315f,0xaf3231ed,0x324fb01d,0x30ecb2dd,0xb3b633f6,0x2c442646,0x33fab3a8,0xa4b5aca5,0xb048326d,0x32c2b0c4,0x3184b33b,0xb1cb2ed7,
0x1e480000,0xb3ff3400,0x2b03aa3e,0xb3ce33d9,0x24b5a248,0xb3fa33fe,0x2c44abc6,0xb3b633c3,0x27d6a646,0xb3f133f6,0x2d05aca5,0xb39933a8,0x2979a8b2,0xb3e233ea,0x2dc2ad64,0xb3773388,
0x2e7c0000,0xb3503400,0xb09b2a3e,0x328ab3d9,0x3399b1ed,0xad05315f,0xb3f132dd,0x27d6b01d,0x32f6b3f6,0x2fe3a646,0xb20f33a8,0xb13a2ca5,0x2b03b0c4,0x33ceb26d,0x9e482ed7,0xb3ff333b,
0x31cb0000,0xb1843400,0x32c2aa3e,0xb04833d9,0x313ab3fe,0x320fa248,0x2fe3b3c3,0x32f6abc6,0xb24f2646,0x30ecb3f6,0xb3252ca5,0x2f32b3a8,0xb09b33ea,0xb28a28b2,0xae7c3388,0xb3502d64,
0x33770000,0xadc23400,0xb3e22a3e,0x2979b3d9,0xaf32b15f,0x3325b1ed,0x30ec301d,0xb24f32dd,0xac4433f6,0xb3b62646,0x24b5b3a8,0x33faaca5,0x32c2b26d,0x304830c4,0xb1cb333b,0xb184aed7,
0x33ff0000,0x1e483400,0x33ceaa3e,0x2b0333d9,0xb3fa2248,0xa4b5b3fe,0xb3b62bc6,0xac44b3c3,0x33f1a646,0x27d633f6,0x3399aca5,0x2d0533a8,0xb3e228b2,0xa979b3ea,0xb3772d64,0xadc2b388,
0x33500000,0x2e7c3400,0xb28a2a3e,0xb09bb3d9,0xad0531ed,0xb399b15f,0x27d6b2dd,0x33f1301d,0xafe3b3f6,0x32f6a646,0x313a33a8,0xb20f2ca5,0x33ce30c4,0xab03326d,0xb3ffaed7,0x1e48b33b,
0x31840000,0x31cb3400,0x3048aa3e,0x32c233d9,0x320f33fe,0xb13a2248,0x32f633c3,0xafe32bc6,0xb0ec2646,0xb24fb3f6,0xaf322ca5,0xb325b3a8,0xb28ab3ea,0x309ba8b2,0xb350b388,0x2e7cad64,
0x2dc20000,0x33773400,0xa9792a3e,0xb3e2b3d9,0x3325315f,0x2f3231ed,0xb24fb01d,0xb0ecb2dd,0x33b633f6,0xac442646,0xb3fab3a8,0x24b5aca5,0x3048326d,0xb2c2b0c4,0xb184b33b,0x31cb2ed7,
0x0,0x34003400,0xb21f0000,0x37643800,0x0,0x34003400,0xb764b5a8,0x321f35a8,0x0,0x34003400,0xb764b800,0xb21f0000,0x0,0x34003400,0xb21fb5a8,0xb764b5a8,
0xb364ae1f,0x2e1f3364,0xb7640000,0x321f3800,0xae1fb364,0xb364ae1f,0x321fb5a8,0xb764b5a8,0x33642e1f,0xae1fb364,0x321f3800,0x37648000,0x2e1f3364,0x33642e1f,0xb764b5a8,0xb21f35a8,
0xb1a8b1a8,0xb1a831a8,0xb7640000,0xb21f3800,0x31a831a8,0x31a8b1a8,0x321f35a8,0x3764b5a8,0xb1a8b1a8,0xb1a831a8,0x321fb800,0xb7640000,0x31a831a8,0x31a8b1a8,0xb76435a8,0x321f35a8,
0x2e1fb364,0xb3642e1f,0xb21f0000,0xb7643800,0xb3642e1f,0xae1f3364,0xb76435a8,0xb21f35a8,0xae1f3364,0x3364ae1f,0xb7643800,0x321f8000,0x3364ae1f,0x2e1fb364,0xb21f35a8,0x3764b5a8,
0x3400b400,0x80000000,0x321f0000,0xb7643800,0x3400b400,0x80000000,0x3764b5a8,0xb21f35a8,0x3400b400,0x80000000,0x3764b800,0x321f0000,0x3400b400,0x80000000,0x321fb5a8,0x3764b5a8,
0x2e1fb364,0x3364ae1f,0x37640000,0xb21f3800,0xb3642e1f,0x2e1fb364,0xb21fb5a8,0x3764b5a8,0xae1f3364,0xb3642e1f,0xb21f3800,0xb7648000,0x3364ae1f,0xae1f3364,0x3764b5a8,0x321f35a8,
0xb1a8b1a8,0x31a8b1a8,0x37640000,0x321f3800,0x31a831a8,0xb1a831a8,0xb21f35a8,0xb764b5a8,0xb1a8b1a8,0x31a8b1a8,0xb21fb800,0x37640000,0x31a831a8,0xb1a831a8,0x376435a8,0xb21f35a8,
0xb364ae1f,0xae1fb364,0x321f0000,0x37643800,0xae1fb364,0x33642e1f,0x376435a8,0x321f35a8,0x33642e1f,0x2e1f3364,0x37643800,0xb21f8000,0x2e1f3364,0xb364ae1f,0x321f35a8,0xb764b5a8,
0x0,0x2b03ab03,0x34003400,0xb3ce33ce,0x0,0x2b03ab03,0x34003400,0xb3ce33ce,0x0,0x2b03ab03,0x34003400,0xb3ce33ce,0x0,0x2b03ab03,0x34003400,0xb3ce33ce,
0xae879f11,0x30c9abdf,0x334e33ff,0xb26933c1,0xb379b1d0,0x33ebb2e0,0x2db63180,0xa8993017,0xb34eb3ff,0x3269b3c1,0xae879f11,0x30c9abdf,0xadb6b180,0x2899b017,0xb379b1d0,0x33ebb2e0,
0xb1f6a311,0x32fcac5d,0x315633fd,0xafcd33b2,0xb156b3fd,0x2fcdb3b2,0xb1f6a311,0x32fcac5d,0x31f62311,0xb2fc2c5d,0xb156b3fd,0x2fcdb3b2,0x315633fd,0xafcd33b2,0x31f62311,0xb2fc2c5d,
0xb39ea54c,0x33f8acc9,0x2ce133f9,0xa5b033a2,0x2f53b12b,0xb122af6a,0xb31db21b,0x3223b317,0x2ce133f9,0xa5b033a2,0x339e254c,0xb3f82cc9,0xb31db21b,0x3223b317,0xaf53312b,0x31222f6a,
0xb3f4a70e,0x3391ad34,0xa70e33f4,0x2d343391,0x33f4270e,0xb3912d34,0x270eb3f4,0xad34b391,0xb3f4a70e,0x3391ad34,0xa70e33f4,0x2d343391,0x33f4270e,0xb3912d34,0x270eb3f4,0xad34b391,
0xb2e6a867,0x31d8ad9f,0xb00d33ed,0x3176337d,0x2c083262,0xa0523349,0x33beb0d3,0xb3ffae9e,0x300db3ed,0xb176b37d,0xb2e6a867,0x31d8ad9f,0xb3be30d3,0x33ff2e9e,0x2c083262,0xa0523349,
0xb0a6a947,0x2e37ae08,0xb28333e4,0x335f3369,0xb28333e4,0x335f3369,0x30a62947,0xae372e08,0x30a62947,0xae372e08,0x3283b3e4,0xb35fb369,0x3283b3e4,0xb35fb369,0xb0a6a947,0x2e37ae08,
0xaa57aa26,0x9d7fae70,0xb3d733da,0x34003353,0xb2aa3077,0x31892dce,0xb06d32a3,0x31c73374,0xb3d733da,0x34003353,0x2a572a26,0x1d7f2e70,0xb06d32a3,0x31c73374,0x32aab077,0xb189adce,
0x0,0x2b03ab03,0x34003400,0xb3ce33ce,0x0,0x2b03ab03,0x34003400,0xb3ce33ce,0x0,0x2b03ab03,0x34003400,0xb3ce33ce,0x0,0x2b03ab03,0x34003400,0xb3ce33ce,
0x2e871f11,0xb0c92bdf,0xb34eb3ff,0x3269b3c1,0x337931d0,0xb3eb32e0,0xadb6b180,0x2899b017,0x334e33ff,0xb26933c1,0x2e871f11,0xb0c92bdf,0x2db63180,0xa8993017,0x337931d0,0xb3eb32e0,
0xb1f6a311,0x32fcac5d,0x315633fd,0xafcd33b2,0xb156b3fd,0x2fcdb3b2,0xb1f6a311,0x32fcac5d,0x31f62311,0xb2fc2c5d,0xb156b3fd,0x2fcdb3b2,0x315633fd,0xafcd33b2,0x31f62311,0xb2fc2c5d,
0x339e254c,0xb3f82cc9,0xace1b3f9,0x25b0b3a2,0xaf53312b,0x31222f6a,0x331d321b,0xb2233317,0xace1b3f9,0x25b0b3a2,0xb39ea54c,0x33f8acc9,0x331d321b,0xb2233317,0x2f53b12b,0xb122af6a,
0xb3f4a70e,0x3391ad34,0xa70e33f4,0x2d343391,0x33f4270e,0xb3912d34,0x270eb3f4,0xad34b391,0xb3f4a70e,0x3391ad34,0xa70e33f4,0x2d343391,0x33f4270e,0xb3912d34,0x270eb3f4,0xad34b391,
0x32e62867,0xb1d82d9f,0x300db3ed,0xb176b37d,0xac08b262,0x2052b349,0xb3be30d3,0x33ff2e9e,0xb00d33ed,0x3176337d,0x32e62867,0xb1d82d9f,0x33beb0d3,0xb3ffae9e,0xac08b262,0x2052b349,
0xb0a6a947,0x2e37ae08,0xb28333e4,0x335f3369,0xb28333e4,0x335f3369,0x30a62947,0xae372e08,0x30a62947,0xae372e08,0x3283b3e4,0xb35fb369,0x3283b3e4,0xb35fb369,0xb0a6a947,0x2e37ae08,
0x2a572a26,0x1d7f2e70,0x33d7b3da,0xb400b353,0x32aab077,0xb189adce,0x306db2a3,0xb1c7b374,0x33d7b3da,0xb400b353,0xaa57aa26,0x9d7fae70,0x306db2a3,0xb1c7b374,0xb2aa3077,0x31892dce,
0x9f110000,0x33ff3400,0xabdfab03,0x33c133ce,0xa54ca311,0x33f933fd,0xacc9ac5d,0x33a233b2,0xa867a70e,0x33ed33f4,0xad9fad34,0x337d3391,0xaa26a947,0x33da33e4,0xae70ae08,0x33533369,
0xae870000,0x334e3400,0x30c92b03,0xb269b3ce,0xb39eb1f6,0x2ce13156,0x33f832fc,0xa5b0afcd,0xb2e6b3f4,0xb00da70e,0x31d83391,0x31762d34,0xaa57b0a6,0xb3d7b283,0x9d7f2e37,0x3400335f,
0xb1d00000,0x31803400,0xb2e0ab03,0x301733ce,0xb12bb3fd,0xb21ba311,0xaf6ab3b2,0xb317ac5d,0x3262270e,0xb0d3b3f4,0x33492d34,0xae9eb391,0x307733e4,0x32a32947,0x2dce3369,0x33742e08,
0xb3790000,0x2db63400,0x33eb2b03,0xa899b3ce,0x2f53b156,0xb31db1f6,0xb1222fcd,0x322332fc,0x2c0833f4,0x33be270e,0xa052b391,0xb3ffad34,0xb2aab283,0xb06d30a6,0x3189335f,0x31c7ae37,
0xb3ff0000,0x9f113400,0xb3c1ab03,0xabdf33ce,0x33f92311,0x254cb3fd,0x33a22c5d,0x2cc9b3b2,0xb3eda70e,0xa86733f4,0xb37dad34,0xad9f3391,0x33da2947,0x2a26b3e4,0x33532e08,0x2e70b369,
0xb34e0000,0xae873400,0x32692b03,0x30c9b3ce,0x2ce131f6,0x339eb156,0xa5b0b2fc,0xb3f82fcd,0x300db3f4,0xb2e6a70e,0xb1763391,0x31d82d34,0xb3d730a6,0x2a573283,0x3400ae37,0x1d7fb35f,
0xb1800000,0xb1d03400,0xb017ab03,0xb2e033ce,0xb21b33fd,0x312b2311,0xb31733b2,0x2f6a2c5d,0x30d3270e,0x3262b3f4,0x2e9e2d34,0x3349b391,0x32a3b3e4,0xb077a947,0x3374b369,0xadceae08,
0xadb60000,0xb3793400,0x28992b03,0x33ebb3ce,0xb31d3156,0xaf5331f6,0x3223afcd,0x3122b2fc,0xb3be33f4,0x2c08270e,0x33ffb391,0xa052ad34,0xb06d3283,0x32aab0a6,0x31c7b35f,0xb1892e37,
0x1f110000,0xb3ff3400,0x2bdfab03,0xb3c133ce,0x254ca311,0xb3f933fd,0x2cc9ac5d,0xb3a233b2,0x2867a70e,0xb3ed33f4,0x2d9fad34,0xb37d3391,0x2a26a947,0xb3da33e4,0x2e70ae08,0xb3533369,
0x2e870000,0xb34e3400,0xb0c92b03,0x3269b3ce,0x339eb1f6,0xace13156,0xb3f832fc,0x25b0afcd,0x32e6b3f4,0x300da70e,0xb1d83391,0xb1762d34,0x2a57b0a6,0x33d7b283,0x1d7f2e37,0xb400335f,
0x31d00000,0xb1803400,0x32e0ab03,0xb01733ce,0x312bb3fd,0x321ba311,0x2f6ab3b2,0x3317ac5d,0xb262270e,0x30d3b3f4,0xb3492d34,0x2e9eb391,0xb07733e4,0xb2a32947,0xadce3369,0xb3742e08,
0x33790000,0xadb63400,0xb3eb2b03,0x2899b3ce,0xaf53b156,0x331db1f6,0x31222fcd,0xb22332fc,0xac0833f4,0xb3be270e,0x2052b391,0x33ffad34,0x32aab283,0x306d30a6,0xb189335f,0xb1c7ae37,
0x33ff0000,0x1f113400,0x33c1ab03,0x2bdf33ce,0xb3f92311,0xa54cb3fd,0xb3a22c5d,0xacc9b3b2,0x33eda70e,0x286733f4,0x337dad34,0x2d9f3391,0xb3da2947,0xaa26b3e4,0xb3532e08,0xae70b369,
0x334e0000,0x2e873400,0xb2692b03,0xb0c9b3ce,0xace131f6,0xb39eb156,0x25b0b2fc,0x33f82fcd,0xb00db3f4,0x32e6a70e,0x31763391,0xb1d82d34,0x33d730a6,0xaa573283,0xb400ae37,0x9d7fb35f,
0x31800000,0x31d03400,0x3017ab03,0x32e033ce,0x321b33fd,0xb12b2311,0x331733b2,0xaf6a2c5d,0xb0d3270e,0xb262b3f4,0xae9e2d34,0xb349b391,0xb2a3b3e4,0x3077a947,0xb374b369,0x2dceae08,
0x2db60000,0x33793400,0xa8992b03,0xb3ebb3ce,0x331d3156,0x2f5331f6,0xb223afcd,0xb122b2fc,0x33be33f4,0xac08270e,0xb3ffb391,0x2052ad34,0x306d3283,0xb2aab0a6,0xb1c7b35f,0x31892e37,
0x0,0x34003400,0xb2d70000,0x373b3800,0x0,0x34003400,0xb7c3b62f,0x2fc63513,0x0,0x34003400,0xb66db7d9,0xb4c4ae3e,0x0,0x34003400,0xa648b38b,0xb7feb70e,
0xb388aed7,0x2d64333b,0xb7880000,0x31643800,0xad64b33b,0xb388aed7,0x341db513,0xb6ddb62f,0x33882ed7,0xad64b33b,0x2cb237d9,0x37ea2e3e,0x2d64333b,0x33882ed7,0xb5edb70e,0xb55f338b,
0xb113b22f,0xb22f3113,0xb73b0000,0xb2d73800,0x3113322f,0x322fb113,0x2fc6362f,0x37c3b513,0xb113b22f,0xb22f3113,0x34c4b7d9,0xb66dae3e,0x3113322f,0x322fb113,0xb7fe338b,0x2648370e,
0x301db3c3,0xb2dd2bc6,0xb1640000,0xb7883800,0xb2dd2bc6,0xb01d33c3,0xb6dd3513,0xb41d362f,0xb01d33c3,0x32ddabc6,0xb7ea37d9,0x2cb22e3e,0x32ddabc6,0x301db3c3,0xb55f370e,0x35edb38b,
0x33d9b3d9,0x2a3eaa3e,0x32d70000,0xb73b3800,0x33d9b3d9,0x2a3eaa3e,0x37c3b62f,0xafc63513,0x33d9b3d9,0x2a3eaa3e,0x366db7d9,0x34c4ae3e,0x33d9b3d9,0x2a3eaa3e,0x2648b38b,0x37feb70e,
0x28b2b26d,0x33eab0c4,0x37880000,0xb1643800,0xb3ea30c4,0x28b2b26d,0xb41db513,0x36ddb62f,0xa8b2326d,0xb3ea30c4,0xacb237d9,0xb7ea2e3e,0x33eab0c4,0xa8b2326d,0x35edb70e,0x355f338b,
0xb30eaf8b,0x2f8bb30e,0x373b0000,0x32d73800,0x330e2f8b,0xaf8b330e,0xafc6362f,0xb7c3b513,0xb30eaf8b,0x2f8bb30e,0xb4c4b7d9,0x366dae3e,0x330e2f8b,0xaf8b330e,0x37fe338b,0xa648370e,
0xb1eda248,0xb15fb3fe,0x31640000,0x37883800,0xb15fb3fe,0x31ed2248,0x36dd3513,0x341d362f,0x31ed2248,0x315f33fe,0x37ea37d9,0xacb22e3e,0x315f33fe,0xb1eda248,0x355f370e,0xb5edb38b,
0x0,0x2bc6abc6,0x34003400,0xb3c333c3,0x0,0x2bc6abc6,0x34003400,0xb3c333c3,0x0,0x2bc6abc6,0x34003400,0xb3c333c3,0x0,0x2bc6abc6,0x34003400,0xb3c333c3,
0xae939fda,0x30f6ac5d,0x334b33ff,0xb24733b2,0xb37bb1d4,0x33f2b2fc,0x2dab317b,0xa7722fcd,0xb34bb3ff,0x3247b3b2,0xae939fda,0x30f6ac5d,0xadabb17b,0x2772afcd,0xb37bb1d4,0x33f2b2fc,
0xb1fea3d9,0x331aacd5,0x314d33fc,0xaf5e33a0,0xb14db3fc,0x2f5eb3a0,0xb1fea3d9,0x331aacd5,0x31fe23d9,0xb31a2cd5,0xb14db3fc,0x2f5eb3a0,0x314d33fc,0xaf5e33a0,0x31fe23d9,0xb31a2cd5,
0xb3a4a5e2,0x33fdad4c,0x2cbd33f7,0xa311338c,0x2f75b11d,0xb156aeee,0xb314b227,0x31f6b336,0x2cbd33f7,0xa311338c,0x33a425e2,0xb3fd2d4c,0xb314b227,0x31f6b336,0xaf75311d,0x31562eee,
0xb3f1a7d6,0x3377adc2,0xa7d633f1,0x2dc23377,0x33f127d6,0xb3772dc2,0x27d6b3f1,0xadc2b377,0xb3f1a7d6,0x3377adc2,0xa7d633f1,0x2dc23377,0x33f127d6,0xb3772dc2,0x27d6b3f1,0xadc2b377,
0xb2d6a8e4,0x319fae37,0xb02833e8,0x31b1335f,0x2b963274,0x16483369,0x33c6b0ba,0xb400ae08,0x3028b3e8,0xb1b1b35f,0xb2d6a8e4,0x319fae37,0xb3c630ba,0x34002e08,0x2b963274,0x16483369,
0xb087a9db,0x2d93aeaa,0xb29933dd,0x33803346,0xb29933dd,0x33803346,0x308729db,0xad932eaa,0x308729db,0xad932eaa,0x3299b3dd,0xb380b346,0x3299b3dd,0xb380b346,0xb087a9db,0x2d93aeaa,
0xa9aaaad2,0xa451af1b,0xb3e033d1,0x33fb332b,0xb2923052,0x31432d1d,0xb09132bc,0x32073395,0xb3e033d1,0x33fb332b,0x29aa2ad2,0x24512f1b,0xb09132bc,0x32073395,0x3292b052,0xb143ad1d,
0x0,0x2bc6abc6,0x34003400,0xb3c333c3,0x0,0x2bc6abc6,0x34003400,0xb3c333c3,0x0,0x2bc6abc6,0x34003400,0xb3c333c3,0x0,0x2bc6abc6,0x34003400,0xb3c333c3,
0x2e931fda,0xb0f62c5d,0xb34bb3ff,0x3247b3b2,0x337b31d4,0xb3f232fc,0xadabb17b,0x2772afcd,0x334b33ff,0xb24733b2,0x2e931fda,0xb0f62c5d,0x2dab317b,0xa7722fcd,0x337b31d4,0xb3f232fc,
0xb1fea3d9,0x331aacd5,0x314d33fc,0xaf5e33a0,0xb14db3fc,0x2f5eb3a0,0xb1fea3d9,0x331aacd5,0x31fe23d9,0xb31a2cd5,0xb14db3fc,0x2f5eb3a0,0x314d33fc,0xaf5e33a0,0x31fe23d9,0xb31a2cd5,
0x33a425e2,0xb3fd2d4c,0xacbdb3f7,0x2311b38c,0xaf75311d,0x31562eee,0x33143227,0xb1f63336,0xacbdb3f7,0x2311b38c,0xb3a4a5e2,0x33fdad4c,0x33143227,0xb1f63336,0x2f75b11d,0xb156aeee,
0xb3f1a7d6,0x3377adc2,0xa7d633f1,0x2dc23377,0x33f127d6,0xb3772dc2,0x27d6b3f1,0xadc2b377,0xb3f1a7d6,0x3377adc2,0xa7d633f1,0x2dc23377,0x33f127d6,0xb3772dc2,0x27d6b3f1,0xadc2b377,
0x32d628e4,0xb19f2e37,0x3028b3e8,0xb1b1b35f,0xab96b274,0x9648b369,0xb3c630ba,0x34002e08,0xb02833e8,0x31b1335f,0x32d628e4,0xb19f2e37,0x33c6b0ba,0xb400ae08,0xab96b274,0x9648b369,
0xb087a9db,0x2d93aeaa,0xb29933dd,0x33803346,0xb29933dd,0x33803346,0x308729db,0xad932eaa,0x308729db,0xad932eaa,0x3299b3dd,0xb380b346,0x3299b3dd,0xb380b346,0xb087a9db,0x2d93aeaa,
0x29aa2ad2,0x24512f1b,0x33e0b3d1,0xb3fbb32b,0x3292b052,0xb143ad1d,0x3091b2bc,0xb207b395,0x33e0b3d1,0xb3fbb32b,0xa9aaaad2,0xa451af1b,0x3091b2bc,0xb207b395,0xb2923052,0x31432d1d,
0x9fda0000,0x33ff3400,0xac5dabc6,0x33b233c3,0xa5e2a3d9,0x33f733fc,0xad4cacd5,0x338c33a0,0xa8e4a7d6,0x33e833f1,0xae37adc2,0x335f3377,0xaad2a9db,0x33d133dd,0xaf1baeaa,0x332b3346,
0xae930000,0x334b3400,0x30f62bc6,0xb247b3c3,0xb3a4b1fe,0x2cbd314d,0x33fd331a,0xa311af5e,0xb2d6b3f1,0xb028a7d6,0x319f3377,0x31b12dc2,0xa9aab087,0xb3e0b299,0xa4512d93,0x33fb3380,
0xb1d40000,0x317b3400,0xb2fcabc6,0x2fcd33c3,0xb11db3fc,0xb227a3d9,0xaeeeb3a0,0xb336acd5,0x327427d6,0xb0bab3f1,0x33692dc2,0xae08b377,0x305233dd,0x32bc29db,0x2d1d3346,0x33952eaa,
0xb37b0000,0x2dab3400,0x33f22bc6,0xa772b3c3,0x2f75b14d,0xb314b1fe,0xb1562f5e,0x31f6331a,0x2b9633f1,0x33c627d6,0x1648b377,0xb400adc2,0xb292b299,0xb0913087,0x31433380,0x3207ad93,
0xb3ff0000,0x9fda3400,0xb3b2abc6,0xac5d33c3,0x33f723d9,0x25e2b3fc,0x338c2cd5,0x2d4cb3a0,0xb3e8a7d6,0xa8e433f1,0xb35fadc2,0xae373377,0x33d129db,0x2ad2b3dd,0x332b2eaa,0x2f1bb346,
0xb34b0000,0xae933400,0x32472bc6,0x30f6b3c3,0x2cbd31fe,0x33a4b14d,0xa311b31a,0xb3fd2f5e,0x3028b3f1,0xb2d6a7d6,0xb1b13377,0x319f2dc2,0xb3e03087,0x29aa3299,0x33fbad93,0x2451b380,
0xb17b0000,0xb1d43400,0xafcdabc6,0xb2fc33c3,0xb22733fc,0x311d23d9,0xb33633a0,0x2eee2cd5,0x30ba27d6,0x3274b3f1,0x2e082dc2,0x3369b377,0x32bcb3dd,0xb052a9db,0x3395b346,0xad1daeaa,
0xadab0000,0xb37b3400,0x27722bc6,0x33f2b3c3,0xb314314d,0xaf7531fe,0x31f6af5e,0x3156b31a,0xb3c633f1,0x2b9627d6,0x3400b377,0x1648adc2,0xb0913299,0x3292b087,0x3207b380,0xb1432d93,
0x1fda0000,0xb3ff3400,0x2c5dabc6,0xb3b233c3,0x25e2a3d9,0xb3f733fc,0x2d4cacd5,0xb38c33a0,0x28e4a7d6,0xb3e833f1,0x2e37adc2,0xb35f3377,0x2ad2a9db,0xb3d133dd,0x2f1baeaa,0xb32b3346,
0x2e930000,0xb34b3400,0xb0f62bc6,0x3247b3c3,0x33a4b1fe,0xacbd314d,0xb3fd331a,0x2311af5e,0x32d6b3f1,0x3028a7d6,0xb19f3377,0xb1b12dc2,0x29aab087,0x33e0b299,0x24512d93,0xb3fb3380,
0x31d40000,0xb17b3400,0x32fcabc6,0xafcd33c3,0x311db3fc,0x3227a3d9,0x2eeeb3a0,0x3336acd5,0xb27427d6,0x30bab3f1,0xb3692dc2,0x2e08b377,0xb05233dd,0xb2bc29db,0xad1d3346,0xb3952eaa,
0x337b0000,0xadab3400,0xb3f22bc6,0x2772b3c3,0xaf75b14d,0x3314b1fe,0x31562f5e,0xb1f6331a,0xab9633f1,0xb3c627d6,0x9648b377,0x3400adc2,0x3292b299,0x30913087,0xb1433380,0xb207ad93,
0x33ff0000,0x1fda3400,0x33b2abc6,0x2c5d33c3,0xb3f723d9,0xa5e2b3fc,0xb38c2cd5,0xad4cb3a0,0x33e8a7d6,0x28e433f1,0x335fadc2,0x2e373377,0xb3d129db,0xaad2b3dd,0xb32b2eaa,0xaf1bb346,
0x334b0000,0x2e933400,0xb2472bc6,0xb0f6b3c3,0xacbd31fe,0xb3a4b14d,0x2311b31a,0x33fd2f5e,0xb028b3f1,0x32d6a7d6,0x31b13377,0xb19f2dc2,0x33e03087,0xa9aa3299,0xb3fbad93,0xa451b380,
0x317b0000,0x31d43400,0x2fcdabc6,0x32fc33c3,0x322733fc,0xb11d23d9,0x333633a0,0xaeee2cd5,0xb0ba27d6,0xb274b3f1,0xae082dc2,0xb369b377,0xb2bcb3dd,0x3052a9db,0xb395b346,0x2d1daeaa,
0x2dab0000,0x337b3400,0xa7722bc6,0xb3f2b3c3,0x3314314d,0x2f7531fe,0xb1f6af5e,0xb156b31a,0x33c633f1,0xab9627d6,0xb400b377,0x9648adc2,0x30913299,0xb292b087,0xb207b380,0x31432d93,
0x0,0x34003400,0xb38b0000,0x370e3800,0x0,0x34003400,0xb7f6b6a7,0x2a463472,0x0,0x34003400,0xb513b764,0xb62fb21f,0x0,0x34003400,0x30a5ae3e,0xb7a8b7d9,
0xb3a8af8b,0x2ca5330e,0xb7a80000,0x30a53800,0xaca5b30e,0xb3a8af8b,0x3513b472,0xb62fb6a7,0x33a82f8b,0xaca5b30e,0xaa463764,0x37f6321f,0x2ca5330e,0x33a82f8b,0xb38bb7d9,0xb70e2e3e,
0xb072b2a7,0xb2a73072,0xb70e0000,0xb38b3800,0x307232a7,0x32a7b072,0x2a4636a7,0x37f6b472,0xb072b2a7,0xb2a73072,0x362fb764,0xb513b21f,0x307232a7,0x32a7b072,0xb7a82e3e,0xb0a537d9,
0x3113b3f6,0xb22f2646,0xb0a50000,0xb7a83800,0xb22f2646,0xb11333f6,0xb62f3472,0xb51336a7,0xb11333f6,0x322fa646,0xb7f63764,0xaa46321f,0x322fa646,0x3113b3f6,0xb70e37d9,0x338bae3e,
0x3364b364,0x2e1fae1f,0x338b0000,0xb70e3800,0x3364b364,0x2e1fae1f,0x37f6b6a7,0xaa463472,0x3364b364,0x2e1fae1f,0x3513b764,0x362fb21f,0x3364b364,0x2e1fae1f,0xb0a5ae3e,0x37a8b7d9,
0xa646b113,0x33f6b22f,0x37a80000,0xb0a53800,0xb3f6322f,0xa646b113,0xb513b472,0x362fb6a7,0x26463113,0xb3f6322f,0x2a463764,0xb7f6321f,0x33f6b22f,0x26463113,0x338bb7d9,0x370e2e3e,
0xb3d9aa3e,0x2a3eb3d9,0x370e0000,0x338b3800,0x33d92a3e,0xaa3e33d9,0xaa4636a7,0xb7f6b472,0xb3d9aa3e,0x2a3eb3d9,0xb62fb764,0x3513b21f,0x33d92a3e,0xaa3e33d9,0x37a82e3e,0x30a537d9,
0xaf8b2ca5,0xb30eb3a8,0x30a50000,0x37a83800,0xb30eb3a8,0x2f8baca5,0x362f3472,0x351336a7,0x2f8baca5,0x330e33a8,0x37f63764,0x2a46321f,0x330e33a8,0xaf8b2ca5,0x370e37d9,0xb38bae3e,
0x0,0x2c44ac44,0x34003400,0xb3b633b6,0x0,0x2c44ac44,0x34003400,0xb3b633b6,0x0,0x2c44ac44,0x34003400,0xb3b633b6,0x0,0x2c44ac44,0x34003400,0xb3b633b6,
0xae9ea052,0x3122acc9,0x334933ff,0xb22333a2,0xb37db1d8,0x33f8b317,0x2d9f3176,0xa5b02f6a,0xb349b3ff,0x3223b3a2,0xae9ea052,0x3122acc9,0xad9fb176,0x25b0af6a,0xb37db1d8,0x33f8b317,
0xb207a451,0x3336ad4c,0x314333fb,0xaeee338c,0xb143b3fb,0x2eeeb38c,0xb207a451,0x3336ad4c,0x32072451,0xb3362d4c,0xb143b3fb,0x2eeeb38c,0x314333fb,0xaeee338c,0x32072451,0xb3362d4c,
0xb3aaa678,0x3400adce,0x2c9933f6,0x9d7f3374,0x2f96b10e,0xb189ae70,0xb30bb233,0x31c7b353,0x2c9933f6,0x9d7f3374,0x33aa2678,0xb4002dce,0xb30bb233,0x31c7b353,0xaf96310e,0x31892e70,
0xb3eda84e,0x335aae4e,0xa84e33ed,0x2e4e335a,0x33ed284e,0xb35a2e4e,0x284eb3ed,0xae4eb35a,0xb3eda84e,0x335aae4e,0xa84e33ed,0x2e4e335a,0x33ed284e,0xb35a2e4e,0x284eb3ed,0xae4eb35a,
0xb2c6a960,0x3164aecc,0xb04233e3,0x31e9333e,0x2b1b3287,0x21e33386,0x33cdb0a0,0xb3fead70,0x3042b3e3,0xb1e9b33e,0xb2c6a960,0x3164aecc,0xb3cd30a0,0x33fe2d70,0x2b1b3287,0x21e33386,
0xb067aa6f,0x2cedaf48,0xb2ae33d6,0x339d3320,0xb2ae33d6,0x339d3320,0x30672a6f,0xaced2f48,0x30672a6f,0xaced2f48,0x32aeb3d6,0xb39db320,0x32aeb3d6,0xb39db320,0xb067aa6f,0x2cedaf48,
0xa8fdab7d,0xa740afc2,0xb3e733c7,0x33f332ff,0xb278302d,0x30fb2c69,0xb0b532d3,0x324333b1,0xb3e733c7,0x33f332ff,0x28fd2b7d,0x27402fc2,0xb0b532d3,0x324333b1,0x3278b02d,0xb0fbac69,
0x0,0x2c44ac44,0x34003400,0xb3b633b6,0x0,0x2c44ac44,0x34003400,0xb3b633b6,0x0,0x2c44ac44,0x34003400,0xb3b633b6,0x0,0x2c44ac44,0x34003400,0xb3b633b6,
0x2e9e2052,0xb1222cc9,0xb349b3ff,0x3223b3a2,0x337d31d8,0xb3f83317,0xad9fb176,0x25b0af6a,0x334933ff,0xb22333a2,0x2e9e2052,0xb1222cc9,0x2d9f3176,0xa5b02f6a,0x337d31d8,0xb3f83317,
0xb207a451,0x3336ad4c,0x314333fb,0xaeee338c,0xb143b3fb,0x2eeeb38c,0xb207a451,0x3336ad4c,0x32072451,0xb3362d4c,0xb143b3fb,0x2eeeb38c,0x314333fb,0xaeee338c,0x32072451,0xb3362d4c,
0x33aa2678,0xb4002dce,0xac99b3f6,0x1d7fb374,0xaf96310e,0x31892e70,0x330b3233,0xb1c73353,0xac99b3f6,0x1d7fb374,0xb3aaa678,0x3400adce,0x330b3233,0xb1c73353,0x2f96b10e,0xb189ae70,
0xb3eda84e,0x335aae4e,0xa84e33ed,0x2e4e335a,0x33ed284e,0xb35a2e4e,0x284eb3ed,0xae4eb35a,0xb3eda84e,0x335aae4e,0xa84e33ed,0x2e4e335a,0x33ed284e,0xb35a2e4e,0x284eb3ed,0xae4eb35a,
0x32c62960,0xb1642ecc,0x3042b3e3,0xb1e9b33e,0xab1bb287,0xa1e3b386,0xb3cd30a0,0x33fe2d70,0xb04233e3,0x31e9333e,0x32c62960,0xb1642ecc,0x33cdb0a0,0xb3fead70,0xab1bb287,0xa1e3b386,
0xb067aa6f,0x2cedaf48,0xb2ae33d6,0x339d3320,0xb2ae33d6,0x339d3320,0x30672a6f,0xaced2f48,0x30672a6f,0xaced2f48,0x32aeb3d6,0xb39db320,0x32aeb3d6,0xb39db320,0xb067aa6f,0x2cedaf48,
0x28fd2b7d,0x27402fc2,0x33e7b3c7,0xb3f3b2ff,0x3278b02d,0xb0fbac69,0x30b5b2d3,0xb243b3b1,0x33e7b3c7,0xb3f3b2ff,0xa8fdab7d,0xa740afc2,0x30b5b2d3,0xb243b3b1,0xb278302d,0x30fb2c69,
0xa0520000,0x33ff3400,0xacc9ac44,0x33a233b6,0xa678a451,0x33f633fb,0xadcead4c,0x3374338c,0xa960a84e,0x33e333ed,0xaeccae4e,0x333e335a,0xab7daa6f,0x33c733d6,0xafc2af48,0x32ff3320,
0xae9e0000,0x33493400,0x31222c44,0xb223b3b6,0xb3aab207,0x2c993143,0x34003336,0x9d7faeee,0xb2c6b3ed,0xb042a84e,0x3164335a,0x31e92e4e,0xa8fdb067,0xb3e7b2ae,0xa7402ced,0x33f3339d,
0xb1d80000,0x31763400,0xb317ac44,0x2f6a33b6,0xb10eb3fb,0xb233a451,0xae70b38c,0xb353ad4c,0x3287284e,0xb0a0b3ed,0x33862e4e,0xad70b35a,0x302d33d6,0x32d32a6f,0x2c693320,0x33b12f48,
0xb37d0000,0x2d9f3400,0x33f82c44,0xa5b0b3b6,0x2f96b143,0xb30bb207,0xb1892eee,0x31c73336,0x2b1b33ed,0x33cd284e,0x21e3b35a,0xb3feae4e,0xb278b2ae,0xb0b53067,0x30fb339d,0x3243aced,
0xb3ff0000,0xa0523400,0xb3a2ac44,0xacc933b6,0x33f62451,0x2678b3fb,0x33742d4c,0x2dceb38c,0xb3e3a84e,0xa96033ed,0xb33eae4e,0xaecc335a,0x33c72a6f,0x2b7db3d6,0x32ff2f48,0x2fc2b320,
0xb3490000,0xae9e3400,0x32232c44,0x3122b3b6,0x2c993207,0x33aab143,0x9d7fb336,0xb4002eee,0x3042b3ed,0xb2c6a84e,0xb1e9335a,0x31642e4e,0xb3e73067,0x28fd32ae,0x33f3aced,0x2740b39d,
0xb1760000,0xb1d83400,0xaf6aac44,0xb31733b6,0xb23333fb,0x310e2451,0xb353338c,0x2e702d4c,0x30a0284e,0x3287b3ed,0x2d702e4e,0x3386b35a,0x32d3b3d6,0xb02daa6f,0x33b1b320,0xac69af48,
0xad9f0000,0xb37d3400,0x25b02c44,0x33f8b3b6,0xb30b3143,0xaf963207,0x31c7aeee,0x3189b336,0xb3cd33ed,0x2b1b284e,0x33feb35a,0x21e3ae4e,0xb0b532ae,0x3278b067,0x3243b39d,0xb0fb2ced,
0x20520000,0xb3ff3400,0x2cc9ac44,0xb3a233b6,0x2678a451,0xb3f633fb,0x2dcead4c,0xb374338c,0x2960a84e,0xb3e333ed,0x2eccae4e,0xb33e335a,0x2b7daa6f,0xb3c733d6,0x2fc2af48,0xb2ff3320,
0x2e9e0000,0xb3493400,0xb1222c44,0x3223b3b6,0x33aab207,0xac993143,0xb4003336,0x1d7faeee,0x32c6b3ed,0x3042a84e,0xb164335a,0xb1e92e4e,0x28fdb067,0x33e7b2ae,0x27402ced,0xb3f3339d,
0x31d80000,0xb1763400,0x3317ac44,0xaf6a33b6,0x310eb3fb,0x3233a451,0x2e70b38c,0x3353ad4c,0xb287284e,0x30a0b3ed,0xb3862e4e,0x2d70b35a,0xb02d33d6,0xb2d32a6f,0xac693320,0xb3b12f48,
0x337d0000,0xad9f3400,0xb3f82c44,0x25b0b3b6,0xaf96b143,0x330bb207,0x31892eee,0xb1c73336,0xab1b33ed,0xb3cd284e,0xa1e3b35a,0x33feae4e,0x3278b2ae,0x30b53067,0xb0fb339d,0xb243aced,
0x33ff0000,0x20523400,0x33a2ac44,0x2cc933b6,0xb3f62451,0xa678b3fb,0xb3742d4c,0xadceb38c,0x33e3a84e,0x296033ed,0x333eae4e,0x2ecc335a,0xb3c72a6f,0xab7db3d6,0xb2ff2f48,0xafc2b320,
0x33490000,0x2e9e3400,0xb2232c44,0xb122b3b6,0xac993207,0xb3aab143,0x1d7fb336,0x34002eee,0xb042b3ed,0x32c6a84e,0x31e9335a,0xb1642e4e,0x33e73067,0xa8fd32ae,0xb3f3aced,0xa740b39d,
0x31760000,0x31d83400,0x2f6aac44,0x331733b6,0x323333fb,0xb10e2451,0x3353338c,0xae702d4c,0xb0a0284e,0xb287b3ed,0xad702e4e,0xb386b35a,0xb2d3b3d6,0x302daa6f,0xb3b1b320,0x2c69af48,
0x2d9f0000,0x337d3400,0xa5b02c44,0xb3f8b3b6,0x330b3143,0x2f963207,0xb1c7aeee,0xb189b336,0x33cd33ed,0xab1b284e,0xb3feb35a,0xa1e3ae4e,0x30b532ae,0xb278b067,0xb243b39d,0x30fb2ced,
0x0,0x34003400,0xb41d0000,0x36dd3800,0x0,0x34003400,0xb7feb70e,0xa648338b,0x0,0x34003400,0xb2d7b6a7,0xb73bb472,0x0,0x34003400,0x34c42a46,0xb66db7f6,
0xb3c3b01d,0x2bc632dd,0xb7c30000,0x2fc63800,0xabc6b2dd,0xb3c3b01d,0x35edb38b,0xb55fb70e,0x33c3301d,0xabc6b2dd,0xb16436a7,0x37883472,0x2bc632dd,0x33c3301d,0xacb2b7f6,0xb7eaaa46,
0xaf8bb30e,0xb30e2f8b,0xb6dd0000,0xb41d3800,0x2f8b330e,0x330eaf8b,0xa648370e,0x37feb38b,0xaf8bb30e,0xb30e2f8b,0x373bb6a7,0xb2d7b472,0x2f8b330e,0x330eaf8b,0xb66daa46,0xb4c437f6,
0x31edb3fe,0xb15fa248,0xafc60000,0xb7c33800,0xb15fa248,0xb1ed33fe,0xb55f338b,0xb5ed370e,0xb1ed33fe,0x315f2248,0xb78836a7,0xb1643472,0x315f2248,0x31edb3fe,0xb7ea37f6,0x2cb22a46,
0x32a7b2a7,0x3072b072,0x341d0000,0xb6dd3800,0x32a7b2a7,0x3072b072,0x37feb70e,0x2648338b,0x32a7b2a7,0x3072b072,0x32d7b6a7,0x373bb472,0x32a7b2a7,0x3072b072,0xb4c42a46,0x366db7f6,
0xad64aed7,0x3388b33b,0x37c30000,0xafc63800,0xb388333b,0xad64aed7,0xb5edb38b,0x355fb70e,0x2d642ed7,0xb388333b,0x316436a7,0xb7883472,0x3388b33b,0x2d642ed7,0x2cb2b7f6,0x37eaaa46,
0xb3f62646,0xa646b3f6,0x36dd0000,0x341d3800,0x33f6a646,0x264633f6,0x2648370e,0xb7feb38b,0xb3f62646,0xa646b3f6,0xb73bb6a7,0x32d7b472,0x33f6a646,0x264633f6,0x366daa46,0x34c437f6,
0xa8b230c4,0xb3eab26d,0x2fc60000,0x37c33800,0xb3eab26d,0x28b2b0c4,0x355f338b,0x35ed370e,0x28b2b0c4,0x33ea326d,0x378836a7,0x31643472,0x33ea326d,0xa8b230c4,0x37ea37f6,0xacb22a46,
0x0,0x2ca5aca5,0x34003400,0xb3a833a8,0x0,0x2ca5aca5,0x34003400,0xb3a833a8,0x0,0x2ca5aca5,0x34003400,0xb3a833a8,0x0,0x2ca5aca5,0x34003400,0xb3a833a8,
0xaeaaa0b6,0x314dad34,0x334633ff,0xb1fe3391,0xb380b1dc,0x33fcb330,0x2d933172,0xa3d92f05,0xb346b3ff,0x31feb391,0xaeaaa0b6,0x314dad34,0xad93b172,0x23d9af05,0xb380b1dc,0x33fcb330,
0xb20fa4b5,0x3350adc2,0x313a33fa,0xae7c3377,0xb13ab3fa,0x2e7cb377,0xb20fa4b5,0x3350adc2,0x320f24b5,0xb3502dc2,0xb13ab3fa,0x2e7cb377,0x313a33fa,0xae7c3377,0x320f24b5,0xb3502dc2,
0xb3afa70e,0x3400ae4e,0x2c7533f4,0x1a48335a,0x2fb7b100,0xb1baadf1,0xb302b23f,0x3196b36e,0x2c7533f4,0x1a48335a,0x33af270e,0xb4002e4e,0xb302b23f,0x3196b36e,0xafb73100,0x31ba2df1,
0xb3eaa8b2,0x333baed7,0xa8b233ea,0x2ed7333b,0x33ea28b2,0xb33b2ed7,0x28b2b3ea,0xaed7b33b,0xb3eaa8b2,0x333baed7,0xa8b233ea,0x2ed7333b,0x33ea28b2,0xb33b2ed7,0x28b2b3ea,0xaed7b33b,
0xb2b5a9db,0x3127af5e,0xb05d33dd,0x321f331a,0x2aa13299,0x257e33a0,0x33d4b087,0xb3f8acd5,0x305db3dd,0xb21fb31a,0xb2b5a9db,0x3127af5e,0xb3d43087,0x33f82cd5,0x2aa13299,0x257e33a0,
0xb048ab03,0x2c44afe3,0xb2c233ce,0x33b632f6,0xb2c233ce,0x33b632f6,0x30482b03,0xac442fe3,0x30482b03,0xac442fe3,0x32c2b3ce,0xb3b6b2f6,0x32c2b3ce,0xb3b6b2f6,0xb048ab03,0x2c44afe3,
0xa84eac14,0xa915b032,0xb3ed33bc,0x33e632d0,0xb25e3007,0x30b02b65,0xb0d832e9,0x327c33c9,0xb3ed33bc,0x33e632d0,0x284e2c14,0x29153032,0xb0d832e9,0x327c33c9,0x325eb007,0xb0b0ab65,
0x0,0x2ca5aca5,0x34003400,0xb3a833a8,0x0,0x2ca5aca5,0x34003400,0xb3a833a8,0x0,0x2ca5aca5,0x34003400,0xb3a833a8,0x0,0x2ca5aca5,0x34003400,0xb3a833a8,
0x2eaa20b6,0xb14d2d34,0xb346b3ff,0x31feb391,0x338031dc,0xb3fc3330,0xad93b172,0x23d9af05,0x334633ff,0xb1fe3391,0x2eaa20b6,0xb14d2d34,0x2d933172,0xa3d92f05,0x338031dc,0xb3fc3330,
0xb20fa4b5,0x3350adc2,0x313a33fa,0xae7c3377,0xb13ab3fa,0x2e7cb377,0xb20fa4b5,0x3350adc2,0x320f24b5,0xb3502dc2,0xb13ab3fa,0x2e7cb377,0x313a33fa,0xae7c3377,0x320f24b5,0xb3502dc2,
0x33af270e,0xb4002e4e,0xac75b3f4,0x9a48b35a,0xafb73100,0x31ba2df1,0x3302323f,0xb196336e,0xac75b3f4,0x9a48b35a,0xb3afa70e,0x3400ae4e,0x3302323f,0xb196336e,0x2fb7b100,0xb1baadf1,
0xb3eaa8b2,0x333baed7,0xa8b233ea,0x2ed7333b,0x33ea28b2,0xb33b2ed7,0x28b2b3ea,0xaed7b33b,0xb3eaa8b2,0x333baed7,0xa8b233ea,0x2ed7333b,0x33ea28b2,0xb33b2ed7,0x28b2b3ea,0xaed7b33b,
0x32b529db,0xb1272f5e,0x305db3dd,0xb21fb31a,0xaaa1b299,0xa57eb3a0,0xb3d43087,0x33f82cd5,0xb05d33dd,0x321f331a,0x32b529db,0xb1272f5e,0x33d4b087,0xb3f8acd5,0xaaa1b299,0xa57eb3a0,
0xb048ab03,0x2c44afe3,0xb2c233ce,0x33b632f6,0xb2c233ce,0x33b632f6,0x30482b03,0xac442fe3,0x30482b03,0xac442fe3,0x32c2b3ce,0xb3b6b2f6,0x32c2b3ce,0xb3b6b2f6,0xb048ab03,0x2c44afe3,
0x284e2c14,0x29153032,0x33edb3bc,0xb3e6b2d0,0x325eb007,0xb0b0ab65,0x30d8b2e9,0xb27cb3c9,0x33edb3bc,0xb3e6b2d0,0xa84eac14,0xa915b032,0x30d8b2e9,0xb27cb3c9,0xb25e3007,0x30b02b65,
0xa0b60000,0x33ff3400,0xad34aca5,0x339133a8,0xa70ea4b5,0x33f433fa,0xae4eadc2,0x335a3377,0xa9dba8b2,0x33dd33ea,0xaf5eaed7,0x331a333b,0xac14ab03,0x33bc33ce,0xb032afe3,0x32d032f6,
0xaeaa0000,0x33463400,0x314d2ca5,0xb1feb3a8,0xb3afb20f,0x2c75313a,0x34003350,0x1a48ae7c,0xb2b5b3ea,0xb05da8b2,0x3127333b,0x321f2ed7,0xa84eb048,0xb3edb2c2,0xa9152c44,0x33e633b6,
0xb1dc0000,0x31723400,0xb330aca5,0x2f0533a8,0xb100b3fa,0xb23fa4b5,0xadf1b377,0xb36eadc2,0x329928b2,0xb087b3ea,0x33a02ed7,0xacd5b33b,0x300733ce,0x32e92b03,0x2b6532f6,0x33c92fe3,
0xb3800000,0x2d933400,0x33fc2ca5,0xa3d9b3a8,0x2fb7b13a,0xb302b20f,0xb1ba2e7c,0x31963350,0x2aa133ea,0x33d428b2,0x257eb33b,0xb3f8aed7,0xb25eb2c2,0xb0d83048,0x30b033b6,0x327cac44,
0xb3ff0000,0xa0b63400,0xb391aca5,0xad3433a8,0x33f424b5,0x270eb3fa,0x335a2dc2,0x2e4eb377,0xb3dda8b2,0xa9db33ea,0xb31aaed7,0xaf5e333b,0x33bc2b03,0x2c14b3ce,0x32d02fe3,0x3032b2f6,
0xb3460000,0xaeaa3400,0x31fe2ca5,0x314db3a8,0x2c75320f,0x33afb13a,0x1a48b350,0xb4002e7c,0x305db3ea,0xb2b5a8b2,0xb21f333b,0x31272ed7,0xb3ed3048,0x284e32c2,0x33e6ac44,0x2915b3b6,
0xb1720000,0xb1dc3400,0xaf05aca5,0xb33033a8,0xb23f33fa,0x310024b5,0xb36e3377,0x2df12dc2,0x308728b2,0x3299b3ea,0x2cd52ed7,0x33a0b33b,0x32e9b3ce,0xb007ab03,0x33c9b2f6,0xab65afe3,
0xad930000,0xb3803400,0x23d92ca5,0x33fcb3a8,0xb302313a,0xafb7320f,0x3196ae7c,0x31bab350,0xb3d433ea,0x2aa128b2,0x33f8b33b,0x257eaed7,0xb0d832c2,0x325eb048,0x327cb3b6,0xb0b02c44,
0x20b60000,0xb3ff3400,0x2d34aca5,0xb39133a8,0x270ea4b5,0xb3f433fa,0x2e4eadc2,0xb35a3377,0x29dba8b2,0xb3dd33ea,0x2f5eaed7,0xb31a333b,0x2c14ab03,0xb3bc33ce,0x3032afe3,0xb2d032f6,
0x2eaa0000,0xb3463400,0xb14d2ca5,0x31feb3a8,0x33afb20f,0xac75313a,0xb4003350,0x9a48ae7c,0x32b5b3ea,0x305da8b2,0xb127333b,0xb21f2ed7,0x284eb048,0x33edb2c2,0x29152c44,0xb3e633b6,
0x31dc0000,0xb1723400,0x3330aca5,0xaf0533a8,0x3100b3fa,0x323fa4b5,0x2df1b377,0x336eadc2,0xb29928b2,0x3087b3ea,0xb3a02ed7,0x2cd5b33b,0xb00733ce,0xb2e92b03,0xab6532f6,0xb3c92fe3,
0x33800000,0xad933400,0xb3fc2ca5,0x23d9b3a8,0xafb7b13a,0x3302b20f,0x31ba2e7c,0xb1963350,0xaaa133ea,0xb3d428b2,0xa57eb33b,0x33f8aed7,0x325eb2c2,0x30d83048,0xb0b033b6,0xb27cac44,
0x33ff0000,0x20b63400,0x3391aca5,0x2d3433a8,0xb3f424b5,0xa70eb3fa,0xb35a2dc2,0xae4eb377,0x33dda8b2,0x29db33ea,0x331aaed7,0x2f5e333b,0xb3bc2b03,0xac14b3ce,0xb2d02fe3,0xb032b2f6,
0x33460000,0x2eaa3400,0xb1fe2ca5,0xb14db3a8,0xac75320f,0xb3afb13a,0x9a48b350,0x34002e7c,0xb05db3ea,0x32b5a8b2,0x321f333b,0xb1272ed7,0x33ed3048,0xa84e32c2,0xb3e6ac44,0xa915b3b6,
0x31720000,0x31dc3400,0x2f05aca5,0x333033a8,0x323f33fa,0xb10024b5,0x336e3377,0xadf12dc2,0xb08728b2,0xb299b3ea,0xacd52ed7,0xb3a0b33b,0xb2e9b3ce,0x3007ab03,0xb3c9b2f6,0x2b65afe3,
0x2d930000,0x33803400,0xa3d92ca5,0xb3fcb3a8,0x3302313a,0x2fb7320f,0xb196ae7c,0xb1bab350,0x33d433ea,0xaaa128b2,0xb3f8b33b,0xa57eaed7,0x30d832c2,0xb25eb048,0xb27cb3b6,0x30b02c44,
0x0,0x34003400,0xb4720000,0x36a73800,0x0,0x34003400,0xb7d9b764,0xae3e321f,0x0,0x34003400,0xae3eb5a8,0xb7d9b5a8,0x0,0x34003400,0x36a7321f,0xb472b764,
0xb3d9b072,0x2a3e32a7,0xb7d90000,0x2e3e3800,0xaa3eb2a7,0xb3d9b072,0x36a7b21f,0xb472b764,0x33d93072,0xaa3eb2a7,0xb47235a8,0x36a735a8,0x2a3e32a7,0x33d93072,0x2e3eb764,0xb7d9b21f,
0xae1fb364,0xb3642e1f,0xb6a70000,0xb4723800,0x2e1f3364,0x3364ae1f,0xae3e3764,0x37d9b21f,0xae1fb364,0xb3642e1f,0x37d9b5a8,0xae3eb5a8,0x2e1f3364,0x3364ae1f,0xb472b21f,0xb6a73764,
0x32a7b3d9,0xb072aa3e,0xae3e0000,0xb7d93800,0xb072aa3e,0xb2a733d9,0xb472321f,0xb6a73764,0xb2a733d9,0x30722a3e,0xb6a735a8,0xb47235a8,0x30722a3e,0x32a7b3d9,0xb7d93764,0xae3e321f,
0x31a8b1a8,0x31a8b1a8,0x34720000,0xb6a73800,0x31a8b1a8,0x31a8b1a8,0x37d9b764,0x2e3e321f,0x31a8b1a8,0x31a8b1a8,0x2e3eb5a8,0x37d9b5a8,0x31a8b1a8,0x31a8b1a8,0xb6a7321f,0x3472b764,
0xb072aa3e,0x32a7b3d9,0x37d90000,0xae3e3800,0xb2a733d9,0xb072aa3e,0xb6a7b21f,0x3472b764,0x30722a3e,0xb2a733d9,0x347235a8,0xb6a735a8,0x32a7b3d9,0x30722a3e,0xae3eb764,0x37d9b21f,
0xb3642e1f,0xae1fb364,0x36a70000,0x34723800,0x3364ae1f,0x2e1f3364,0x2e3e3764,0xb7d9b21f,0xb3642e1f,0xae1fb364,0xb7d9b5a8,0x2e3eb5a8,0x3364ae1f,0x2e1f3364,0x3472b21f,0x36a73764,
0x2a3e32a7,0xb3d9b072,0x2e3e0000,0x37d93800,0xb3d9b072,0xaa3eb2a7,0x3472321f,0x36a73764,0xaa3eb2a7,0x33d93072,0x36a735a8,0x347235a8,0x33d93072,0x2a3e32a7,0x37d93764,0x2e3e321f,
0x0,0x2d05ad05,0x34003400,0xb3993399,0x0,0x2d05ad05,0x34003400,0xb3993399,0x0,0x2d05ad05,0x34003400,0xb3993399,0x0,0x2d05ad05,0x34003400,0xb3993399,
0xaeb5a11b,0x3176ad9f,0x334333fe,0xb1d8337d,0xb382b1e1,0x33ffb349,0x2d87316d,0xa0522e9e,0xb343b3fe,0x31d8b37d,0xaeb5a11b,0x3176ad9f,0xad87b16d,0x2052ae9e,0xb382b1e1,0x33ffb349,
0xb217a51a,0x3369ae37,0x313033f9,0xae08335f,0xb130b3f9,0x2e08b35f,0xb217a51a,0x3369ae37,0x3217251a,0xb3692e37,0xb130b3f9,0x2e08b35f,0x313033f9,0xae08335f,0x3217251a,0xb3692e37,
0xb3b4a7a4,0x33feaecc,0x2c5133f1,0x21e3333e,0x2fd8b0f1,0xb1e9ad70,0xb2f9b24b,0x3164b386,0x2c5133f1,0x21e3333e,0x33b427a4,0xb3fe2ecc,0xb2f9b24b,0x3164b386,0xafd830f1,0x31e92d70,
0xb3e6a915,0x331aaf5e,0xa91533e6,0x2f5e331a,0x33e62915,0xb31a2f5e,0x2915b3e6,0xaf5eb31a,0xb3e6a915,0x331aaf5e,0xa91533e6,0x2f5e331a,0x33e62915,0xb31a2f5e,0x2915b3e6,0xaf5eb31a,
0xb2a3aa57,0x30e7afee,0xb07733d7,0x325232f3,0x2a2632aa,0x280433b7,0x33dab06d,0xb3f0ac38,0x3077b3d7,0xb252b2f3,0xb2a3aa57,0x30e7afee,0xb3da306d,0x33f02c38,0x2a2632aa,0x280433b7,
0xb028ab96,0x2b34b03d,0xb2d633c6,0x33cb32c9,0xb2d633c6,0x33cb32c9,0x30282b96,0xab34303d,0x30282b96,0xab34303d,0x32d6b3c6,0xb3cbb2c9,0x32d6b3c6,0xb3cbb2c9,0xb028ab96,0x2b34b03d,
0xa740ac69,0xaa88b081,0xb3f333b1,0x33d5329c,0xb2432fc2,0x306229f4,0xb0fb32ff,0x32b133dc,0xb3f333b1,0x33d5329c,0x27402c69,0x2a883081,0xb0fb32ff,0x32b133dc,0x3243afc2,0xb062a9f4,
0x0,0x2d05ad05,0x34003400,0xb3993399,0x0,0x2d05ad05,0x34003400,0xb3993399,0x0,0x2d05ad05,0x34003400,0xb3993399,0x0,0x2d05ad05,0x34003400,0xb3993399,
0x2eb5211b,0xb1762d9f,0xb343b3fe,0x31d8b37d,0x338231e1,0xb3ff3349,0xad87b16d,0x2052ae9e,0x334333fe,0xb1d8337d,0x2eb5211b,0xb1762d9f,0x2d87316d,0xa0522e9e,0x338231e1,0xb3ff3349,
0xb217a51a,0x3369ae37,0x313033f9,0xae08335f,0xb130b3f9,0x2e08b35f,0xb217a51a,0x3369ae37,0x3217251a,0xb3692e37,0xb130b3f9,0x2e08b35f,0x313033f9,0xae08335f,0x3217251a,0xb3692e37,
0x33b427a4,0xb3fe2ecc,0xac51b3f1,0xa1e3b33e,0xafd830f1,0x31e92d70,0x32f9324b,0xb1643386,0xac51b3f1,0xa1e3b33e,0xb3b4a7a4,0x33feaecc,0x32f9324b,0xb1643386,0x2fd8b0f1,0xb1e9ad70,
0xb3e6a915,0x331aaf5e,0xa91533e6,0x2f5e331a,0x33e62915,0xb31a2f5e,0x2915b3e6,0xaf5eb31a,0xb3e6a915,0x331aaf5e,0xa91533e6,0x2f5e331a,0x33e62915,0xb31a2f5e,0x2915b3e6,0xaf5eb31a,
0x32a32a57,0xb0e72fee,0x3077b3d7,0xb252b2f3,0xaa26b2aa,0xa804b3b7,0xb3da306d,0x33f02c38,0xb07733d7,0x325232f3,0x32a32a57,0xb0e72fee,0x33dab06d,0xb3f0ac38,0xaa26b2aa,0xa804b3b7,
0xb028ab96,0x2b34b03d,0xb2d633c6,0x33cb32c9,0xb2d633c6,0x33cb32c9,0x30282b96,0xab34303d,0x30282b96,0xab34303d,0x32d6b3c6,0xb3cbb2c9,0x32d6b3c6,0xb3cbb2c9,0xb028ab96,0x2b34b03d,
0x27402c69,0x2a883081,0x33f3b3b1,0xb3d5b29c,0x3243afc2,0xb062a9f4,0x30fbb2ff,0xb2b1b3dc,0x33f3b3b1,0xb3d5b29c,0xa740ac69,0xaa88b081,0x30fbb2ff,0xb2b1b3dc,0xb2432fc2,0x306229f4,
0xa11b0000,0x33fe3400,0xad9fad05,0x337d3399,0xa7a4a51a,0x33f133f9,0xaeccae37,0x333e335f,0xaa57a915,0x33d733e6,0xafeeaf5e,0x32f3331a,0xac69ab96,0x33b133c6,0xb081b03d,0x329c32c9,
0xaeb50000,0x33433400,0x31762d05,0xb1d8b399,0xb3b4b217,0x2c513130,0x33fe3369,0x21e3ae08,0xb2a3b3e6,0xb077a915,0x30e7331a,0x32522f5e,0xa740b028,0xb3f3b2d6,0xaa882b34,0x33d533cb,
0xb1e10000,0x316d3400,0xb349ad05,0x2e9e3399,0xb0f1b3f9,0xb24ba51a,0xad70b35f,0xb386ae37,0x32aa2915,0xb06db3e6,0x33b72f5e,0xac38b31a,0x2fc233c6,0x32ff2b96,0x29f432c9,0x33dc303d,
0xb3820000,0x2d873400,0x33ff2d05,0xa052b399,0x2fd8b130,0xb2f9b217,0xb1e92e08,0x31643369,0x2a2633e6,0x33da2915,0x2804b31a,0xb3f0af5e,0xb243b2d6,0xb0fb3028,0x306233cb,0x32b1ab34,
0xb3fe0000,0xa11b3400,0xb37dad05,0xad9f3399,0x33f1251a,0x27a4b3f9,0x333e2e37,0x2eccb35f,0xb3d7a915,0xaa5733e6,0xb2f3af5e,0xafee331a,0x33b12b96,0x2c69b3c6,0x329c303d,0x3081b2c9,
0xb3430000,0xaeb53400,0x31d82d05,0x3176b399,0x2c513217,0x33b4b130,0x21e3b369,0xb3fe2e08,0x3077b3e6,0xb2a3a915,0xb252331a,0x30e72f5e,0xb3f33028,0x274032d6,0x33d5ab34,0x2a88b3cb,
0xb16d0000,0xb1e13400,0xae9ead05,0xb3493399,0xb24b33f9,0x30f1251a,0xb386335f,0x2d702e37,0x306d2915,0x32aab3e6,0x2c382f5e,0x33b7b31a,0x32ffb3c6,0xafc2ab96,0x33dcb2c9,0xa9f4b03d,
0xad870000,0xb3823400,0x20522d05,0x33ffb399,0xb2f93130,0xafd83217,0x3164ae08,0x31e9b369,0xb3da33e6,0x2a262915,0x33f0b31a,0x2804af5e,0xb0fb32d6,0x3243b028,0x32b1b3cb,0xb0622b34,
0x211b0000,0xb3fe3400,0x2d9fad05,0xb37d3399,0x27a4a51a,0xb3f133f9,0x2eccae37,0xb33e335f,0x2a57a915,0xb3d733e6,0x2feeaf5e,0xb2f3331a,0x2c69ab96,0xb3b133c6,0x3081b03d,0xb29c32c9,
0x2eb50000,0xb3433400,0xb1762d05,0x31d8b399,0x33b4b217,0xac513130,0xb3fe3369,0xa1e3ae08,0x32a3b3e6,0x3077a915,0xb0e7331a,0xb2522f5e,0x2740b028,0x33f3b2d6,0x2a882b34,0xb3d533cb,
0x31e10000,0xb16d3400,0x3349ad05,0xae9e3399,0x30f1b3f9,0x324ba51a,0x2d70b35f,0x3386ae37,0xb2aa2915,0x306db3e6,0xb3b72f5e,0x2c38b31a,0xafc233c6,0xb2ff2b96,0xa9f432c9,0xb3dc303d,
0x33820000,0xad873400,0xb3ff2d05,0x2052b399,0xafd8b130,0x32f9b217,0x31e92e08,0xb1643369,0xaa2633e6,0xb3da2915,0xa804b31a,0x33f0af5e,0x3243b2d6,0x30fb3028,0xb06233cb,0xb2b1ab34,
0x33fe0000,0x211b3400,0x337dad05,0x2d9f3399,0xb3f1251a,0xa7a4b3f9,0xb33e2e37,0xaeccb35f,0x33d7a915,0x2a5733e6,0x32f3af5e,0x2fee331a,0xb3b12b96,0xac69b3c6,0xb29c303d,0xb081b2c9,
0x33430000,0x2eb53400,0xb1d82d05,0xb176b399,0xac513217,0xb3b4b130,0xa1e3b369,0x33fe2e08,0xb077b3e6,0x32a3a915,0x3252331a,0xb0e72f5e,0x33f33028,0xa74032d6,0xb3d5ab34,0xaa88b3cb,
0x316d0000,0x31e13400,0x2e9ead05,0x33493399,0x324b33f9,0xb0f1251a,0x3386335f,0xad702e37,0xb06d2915,0xb2aab3e6,0xac382f5e,0xb3b7b31a,0xb2ffb3c6,0x2fc2ab96,0xb3dcb2c9,0x29f4b03d,
0x2d870000,0x33823400,0xa0522d05,0xb3ffb399,0x32f93130,0x2fd83217,0xb164ae08,0xb1e9b369,0x33da33e6,0xaa262915,0xb3f0b31a,0xa804af5e,0x30fb32d6,0xb243b028,0xb2b1b3cb,0x30622b34,
0x0,0x34003400,0xb4c40000,0x366d3800,0x0,0x34003400,0xb788b7a8,0xb16430a5,0x0,0x34003400,0x2648b472,0xb7feb6a7,0x0,0x34003400,0x37c33513,0xafc6b62f,
0xb3eab0c4,0x28b2326d,0xb7ea0000,0x2cb23800,0xa8b2b26d,0xb3eab0c4,0x373bb0a5,0xb2d7b7a8,0x33ea30c4,0xa8b2b26d,0xb5ed3472,0x355f36a7,0x28b2326d,0x33ea30c4,0x341db62f,0xb6ddb513,
0xaca5b3a8,0xb3a82ca5,0xb66d0000,0xb4c43800,0x2ca533a8,0x33a8aca5,0xb16437a8,0x3788b0a5,0xaca5b3a8,0xb3a82ca5,0x37feb472,0x2648b6a7,0x2ca533a8,0x33a8aca5,0xafc6b513,0xb7c3362f,
0x333bb388,0xaed7ad64,0xacb20000,0xb7ea3800,0xaed7ad64,0xb33b3388,0xb2d730a5,0xb73b37a8,0xb33b3388,0x2ed72d64,0xb55f3472,0xb5ed36a7,0x2ed72d64,0x333bb388,0xb6dd362f,0xb41d3513,
0x3072b072,0x32a7b2a7,0x34c40000,0xb66d3800,0x3072b072,0x32a7b2a7,0x3788b7a8,0x316430a5,0x3072b072,0x32a7b2a7,0xa648b472,0x37feb6a7,0x3072b072,0x32a7b2a7,0xb7c33513,0x2fc6b62f,
0xb1ed2248,0x315fb3fe,0x37ea0000,0xacb23800,0xb15f33fe,0xb1ed2248,0xb73bb0a5,0x32d7b7a8,0x31eda248,0xb15f33fe,0x35ed3472,0xb55f36a7,0x315fb3fe,0x31eda248,0xb41db62f,0x36ddb513,
0xb22f3113,0xb113b22f,0x366d0000,0x34c43800,0x322fb113,0x3113322f,0x316437a8,0xb788b0a5,0xb22f3113,0xb113b22f,0xb7feb472,0xa648b6a7,0x322fb113,0x3113322f,0x2fc6b513,0x37c3362f,
0x301d33c3,0xb2ddabc6,0x2cb20000,0x37ea3800,0xb2ddabc6,0xb01db3c3,0x32d730a5,0x373b37a8,0xb01db3c3,0x32dd2bc6,0x355f3472,0x35ed36a7,0x32dd2bc6,0x301d33c3,0x36dd362f,0x341d3513,
0x0,0x2d64ad64,0x34003400,0xb3883388,0x0,0x2d64ad64,0x34003400,0xb3883388,0x0,0x2d64ad64,0x34003400,0xb3883388,0x0,0x2d64ad64,0x34003400,0xb3883388,
0xaec1a17f,0x319fae08,0x334133fe,0xb1b13369,0xb384b1e5,0x3400b35f,0x2d7c3169,0x96482e37,0xb341b3fe,0x31b1b369,0xaec1a17f,0x319fae08,0xad7cb169,0x1648ae37,0xb384b1e5,0x3400b35f,
0xb21fa57e,0x3380aeaa,0x312733f8,0xad933346,0xb127b3f8,0x2d93b346,0xb21fa57e,0x3380aeaa,0x321f257e,0xb3802eaa,0xb127b3f8,0x2d93b346,0x312733f8,0xad933346,0x321f257e,0xb3802eaa,
0xb3b9a81d,0x33f9af48,0x2c2c33ef,0x251a3320,0x2ff9b0e2,0xb217aced,0xb2f0b256,0x3130b39d,0x2c2c33ef,0x251a3320,0x33b9281d,0xb3f92f48,0xb2f0b256,0x3130b39d,0xaff930e2,0x32172ced,
0xb3e2a979,0x32f6afe3,0xa97933e2,0x2fe332f6,0x33e22979,0xb2f62fe3,0x2979b3e2,0xafe3b2f6,0xb3e2a979,0x32f6afe3,0xa97933e2,0x2fe332f6,0x33e22979,0xb2f62fe3,0x2979b3e2,0xafe3b2f6,
0xb292aad2,0x30a6b03d,0xb09133d1,0x328332c9,0x29aa32bc,0x294733cb,0x33e0b052,0xb3e4ab34,0x3091b3d1,0xb283b2c9,0xb292aad2,0x30a6b03d,0xb3e03052,0x33e42b34,0x29aa32bc,0x294733cb,
0xb007ac14,0x29dbb087,0xb2e933bc,0x33dd3299,0xb2e933bc,0x33dd3299,0x30072c14,0xa9db3087,0x30072c14,0xa9db3087,0x32e9b3bc,0xb3ddb299,0x32e9b3bc,0xb3ddb299,0xb007ac14,0x29dbb087,
0xa5e2acbd,0xabf7b0ce,0xb3f733a4,0x33c03265,0xb2272f75,0x30122880,0xb11d3314,0x32e333ec,0xb3f733a4,0x33c03265,0x25e22cbd,0x2bf730ce,0xb11d3314,0x32e333ec,0x3227af75,0xb012a880,
0x0,0x2d64ad64,0x34003400,0xb3883388,0x0,0x2d64ad64,0x34003400,0xb3883388,0x0,0x2d64ad64,0x34003400,0xb3883388,0x0,0x2d64ad64,0x34003400,0xb3883388,
0x2ec1217f,0xb19f2e08,0xb341b3fe,0x31b1b369,0x338431e5,0xb400335f,0xad7cb169,0x1648ae37,0x334133fe,0xb1b13369,0x2ec1217f,0xb19f2e08,0x2d7c3169,0x96482e37,0x338431e5,0xb400335f,
0xb21fa57e,0x3380aeaa,0x312733f8,0xad933346,0xb127b3f8,0x2d93b346,0xb21fa57e,0x3380aeaa,0x321f257e,0xb3802eaa,0xb127b3f8,0x2d93b346,0x312733f8,0xad933346,0x321f257e,0xb3802eaa,
0x33b9281d,0xb3f92f48,0xac2cb3ef,0xa51ab320,0xaff930e2,0x32172ced,0x32f03256,0xb130339d,0xac2cb3ef,0xa51ab320,0xb3b9a81d,0x33f9af48,0x32f03256,0xb130339d,0x2ff9b0e2,0xb217aced,
0xb3e2a979,0x32f6afe3,0xa97933e2,0x2fe332f6,0x33e22979,0xb2f62fe3,0x2979b3e2,0xafe3b2f6,0xb3e2a979,0x32f6afe3,0xa97933e2,0x2fe332f6,0x33e22979,0xb2f62fe3,0x2979b3e2,0xafe3b2f6,
0x32922ad2,0xb0a6303d,0x3091b3d1,0xb283b2c9,0xa9aab2bc,0xa947b3cb,0xb3e03052,0x33e42b34,0xb09133d1,0x328332c9,0x32922ad2,0xb0a6303d,0x33e0b052,0xb3e4ab34,0xa9aab2bc,0xa947b3cb,
0xb007ac14,0x29dbb087,0xb2e933bc,0x33dd3299,0xb2e933bc,0x33dd3299,0x30072c14,0xa9db3087,0x30072c14,0xa9db3087,0x32e9b3bc,0xb3ddb299,0x32e9b3bc,0xb3ddb299,0xb007ac14,0x29dbb087,
0x25e22cbd,0x2bf730ce,0x33f7b3a4,0xb3c0b265,0x3227af75,0xb012a880,0x311db314,0xb2e3b3ec,0x33f7b3a4,0xb3c0b265,0xa5e2acbd,0xabf7b0ce,0x311db314,0xb2e3b3ec,0xb2272f75,0x30122880,
0xa17f0000,0x33fe3400,0xae08ad64,0x33693388,0xa81da57e,0x33ef33f8,0xaf48aeaa,0x33203346,0xaad2a979,0x33d133e2,0xb03dafe3,0x32c932f6,0xacbdac14,0x33a433bc,0xb0ceb087,0x32653299,
0xaec10000,0x33413400,0x319f2d64,0xb1b1b388,0xb3b9b21f,0x2c2c3127,0x33f93380,0x251aad93,0xb292b3e2,0xb091a979,0x30a632f6,0x32832fe3,0xa5e2b007,0xb3f7b2e9,0xabf729db,0x33c033dd,
0xb1e50000,0x31693400,0xb35fad64,0x2e373388,0xb0e2b3f8,0xb256a57e,0xacedb346,0xb39daeaa,0x32bc2979,0xb052b3e2,0x33cb2fe3,0xab34b2f6,0x2f7533bc,0x33142c14,0x28803299,0x33ec3087,
0xb3840000,0x2d7c3400,0x34002d64,0x9648b388,0x2ff9b127,0xb2f0b21f,0xb2172d93,0x31303380,0x29aa33e2,0x33e02979,0x2947b2f6,0xb3e4afe3,0xb227b2e9,0xb11d3007,0x301233dd,0x32e3a9db,
0xb3fe0000,0xa17f3400,0xb369ad64,0xae083388,0x33ef257e,0x281db3f8,0x33202eaa,0x2f48b346,0xb3d1a979,0xaad233e2,0xb2c9afe3,0xb03d32f6,0x33a42c14,0x2cbdb3bc,0x32653087,0x30ceb299,
0xb3410000,0xaec13400,0x31b12d64,0x319fb388,0x2c2c321f,0x33b9b127,0x251ab380,0xb3f92d93,0x3091b3e2,0xb292a979,0xb28332f6,0x30a62fe3,0xb3f73007,0x25e232e9,0x33c0a9db,0x2bf7b3dd,
0xb1690000,0xb1e53400,0xae37ad64,0xb35f3388,0xb25633f8,0x30e2257e,0xb39d3346,0x2ced2eaa,0x30522979,0x32bcb3e2,0x2b342fe3,0x33cbb2f6,0x3314b3bc,0xaf75ac14,0x33ecb299,0xa880b087,
0xad7c0000,0xb3843400,0x16482d64,0x3400b388,0xb2f03127,0xaff9321f,0x3130ad93,0x3217b380,0xb3e033e2,0x29aa2979,0x33e4b2f6,0x2947afe3,0xb11d32e9,0x3227b007,0x32e3b3dd,0xb01229db,
0x217f0000,0xb3fe3400,0x2e08ad64,0xb3693388,0x281da57e,0xb3ef33f8,0x2f48aeaa,0xb3203346,0x2ad2a979,0xb3d133e2,0x303dafe3,0xb2c932f6,0x2cbdac14,0xb3a433bc,0x30ceb087,0xb2653299,
0x2ec10000,0xb3413400,0xb19f2d64,0x31b1b388,0x33b9b21f,0xac2c3127,0xb3f93380,0xa51aad93,0x3292b3e2,0x3091a979,0xb0a632f6,0xb2832fe3,0x25e2b007,0x33f7b2e9,0x2bf729db,0xb3c033dd,
0x31e50000,0xb1693400,0x335fad64,0xae373388,0x30e2b3f8,0x3256a57e,0x2cedb346,0x339daeaa,0xb2bc2979,0x3052b3e2,0xb3cb2fe3,0x2b34b2f6,0xaf7533bc,0xb3142c14,0xa8803299,0xb3ec3087,
0x33840000,0xad7c3400,0xb4002d64,0x1648b388,0xaff9b127,0x32f0b21f,0x32172d93,0xb1303380,0xa9aa33e2,0xb3e02979,0xa947b2f6,0x33e4afe3,0x3227b2e9,0x311d3007,0xb01233dd,0xb2e3a9db,
0x33fe0000,0x217f3400,0x3369ad64,0x2e083388,0xb3ef257e,0xa81db3f8,0xb3202eaa,0xaf48b346,0x33d1a979,0x2ad233e2,0x32c9afe3,0x303d32f6,0xb3a42c14,0xacbdb3bc,0xb2653087,0xb0ceb299,
0x33410000,0x2ec13400,0xb1b12d64,0xb19fb388,0xac2c321f,0xb3b9b127,0xa51ab380,0x33f92d93,0xb091b3e2,0x3292a979,0x328332f6,0xb0a62fe3,0x33f73007,0xa5e232e9,0xb3c0a9db,0xabf7b3dd,
0x31690000,0x31e53400,0x2e37ad64,0x335f3388,0x325633f8,0xb0e2257e,0x339d3346,0xaced2eaa,0xb0522979,0xb2bcb3e2,0xab342fe3,0xb3cbb2f6,0xb314b3bc,0x2f75ac14,0xb3ecb299,0x2880b087,
0x2d7c0000,0x33843400,0x96482d64,0xb400b388,0x32f03127,0x2ff9321f,0xb130ad93,0xb217b380,0x33e033e2,0xa9aa2979,0xb3e4b2f6,0xa947afe3,0x311d32e9,0xb227b007,0xb2e3b3dd,0x301229db,
0x0,0x34003400,0xb5130000,0x362f3800,0x0,0x34003400,0xb70eb7d9,0xb38b2e3e,0x0,0x34003400,0x30a5b21f,0xb7a8b764,0x0,0x34003400,0x37f636a7,0x2a46b472,
0xb3f6b113,0x2646322f,0xb7f60000,0x2a463800,0xa646b22f,0xb3f6b113,0x37a8ae3e,0xb0a5b7d9,0x33f63113,0xa646b22f,0xb70e321f,0x338b3764,0x2646322f,0x33f63113,0x362fb472,0xb513b6a7,
0xaa3eb3d9,0xb3d92a3e,0xb62f0000,0xb5133800,0x2a3e33d9,0x33d9aa3e,0xb38b37d9,0x370eae3e,0xaa3eb3d9,0xb3d92a3e,0x37a8b21f,0x30a5b764,0x2a3e33d9,0x33d9aa3e,0x2a46b6a7,0xb7f63472,
0x33a8b30e,0xaca5af8b,0xaa460000,0xb7f63800,0xaca5af8b,0xb3a8330e,0xb0a52e3e,0xb7a837d9,0xb3a8330e,0x2ca52f8b,0xb38b321f,0xb70e3764,0x2ca52f8b,0x33a8b30e,0xb5133472,0xb62f36a7,
0x2e1fae1f,0x3364b364,0x35130000,0xb62f3800,0x2e1fae1f,0x3364b364,0x370eb7d9,0x338b2e3e,0x2e1fae1f,0x3364b364,0xb0a5b21f,0x37a8b764,0x2e1fae1f,0x3364b364,0xb7f636a7,0xaa46b472,
0xb30e2ca5,0x2f8bb3a8,0x37f60000,0xaa463800,0xaf8b33a8,0xb30e2ca5,0xb7a8ae3e,0x30a5b7d9,0x330eaca5,0xaf8b33a8,0x370e321f,0xb38b3764,0x2f8bb3a8,0x330eaca5,0xb62fb472,0x3513b6a7,
0xb07232a7,0xb2a7b072,0x362f0000,0x35133800,0x3072b2a7,0x32a73072,0x338b37d9,0xb70eae3e,0xb07232a7,0xb2a7b072,0xb7a8b21f,0xb0a5b764,0x3072b2a7,0x32a73072,0xaa46b6a7,0x37f63472,
0x322f33f6,0xb1132646,0x2a460000,0x37f63800,0xb1132646,0xb22fb3f6,0x30a52e3e,0x37a837d9,0xb22fb3f6,0x3113a646,0x338b321f,0x370e3764,0x3113a646,0x322f33f6,0x35133472,0x362f36a7,
0x0,0x2dc2adc2,0x34003400,0xb3773377,0x0,0x2dc2adc2,0x34003400,0xb3773377,0x0,0x2dc2adc2,0x34003400,0xb3773377,0x0,0x2dc2adc2,0x34003400,0xb3773377,
0xaecca1e3,0x31c7ae70,0x333e33fe,0xb1893353,0xb386b1e9,0x3400b374,0x2d703164,0x1d7f2dce,0xb33eb3fe,0x3189b353,0xaecca1e3,0x31c7ae70,0xad70b164,0x9d7fadce,0xb386b1e9,0x3400b374,
0xb227a5e2,0x3395af1b,0x311d33f7,0xad1d332b,0xb11db3f7,0x2d1db32b,0xb227a5e2,0x3395af1b,0x322725e2,0xb3952f1b,0xb11db3f7,0x2d1db32b,0x311d33f7,0xad1d332b,0x322725e2,0xb3952f1b,
0xb3bea867,0x33f3afc2,0x2c0833ed,0x274032ff,0x300db0d3,0xb243ac69,0xb2e6b262,0x30fbb3b1,0x2c0833ed,0x274032ff,0x33be2867,0xb3f32fc2,0xb2e6b262,0x30fbb3b1,0xb00d30d3,0x32432c69,
0xb3dda9db,0x32d0b032,0xa9db33dd,0x303232d0,0x33dd29db,0xb2d03032,0x29dbb3dd,0xb032b2d0,0xb3dda9db,0x32d0b032,0xa9db33dd,0x303232d0,0x33dd29db,0xb2d03032,0x29dbb3dd,0xb032b2d0,
0xb27fab4c,0x3062b081,0xb0ab33ca,0x32b1329c,0x292e32cc,0x2a8833dc,0x33e5b038,0xb3d5a9f4,0x30abb3ca,0xb2b1b29c,0xb27fab4c,0x3062b081,0xb3e53038,0x33d529f4,0x292e32cc,0x2a8833dc,
0xafcdac5d,0x2880b0ce,0xb2fc33b2,0x33ec3265,0xb2fc33b2,0x33ec3265,0x2fcd2c5d,0xa88030ce,0x2fcd2c5d,0xa88030ce,0x32fcb3b2,0xb3ecb265,0x32fcb3b2,0xb3ecb265,0xafcdac5d,0x2880b0ce,
0xa483ad11,0xacb1b118,0xb3fb3397,0x33a6322b,0xb20b2f26,0x2f802614,0xb13e3328,0x331133f7,0xb3fb3397,0x33a6322b,0x24832d11,0x2cb13118,0xb13e3328,0x331133f7,0x320baf26,0xaf80a614,
0x0,0x2dc2adc2,0x34003400,0xb3773377,0x0,0x2dc2adc2,0x34003400,0xb3773377,0x0,0x2dc2adc2,0x34003400,0xb3773377,0x0,0x2dc2adc2,0x34003400,0xb3773377,
0x2ecc21e3,0xb1c72e70,0xb33eb3fe,0x3189b353,0x338631e9,0xb4003374,0xad70b164,0x9d7fadce,0x333e33fe,0xb1893353,0x2ecc21e3,0xb1c72e70,0x2d703164,0x1d7f2dce,0x338631e9,0xb4003374,
0xb227a5e2,0x3395af1b,0x311d33f7,0xad1d332b,0xb11db3f7,0x2d1db32b,0xb227a5e2,0x3395af1b,0x322725e2,0xb3952f1b,0xb11db3f7,0x2d1db32b,0x311d33f7,0xad1d332b,0x322725e2,0xb3952f1b,
0x33be2867,0xb3f32fc2,0xac08b3ed,0xa740b2ff,0xb00d30d3,0x32432c69,0x32e63262,0xb0fb33b1,0xac08b3ed,0xa740b2ff,0xb3bea867,0x33f3afc2,0x32e63262,0xb0fb33b1,0x300db0d3,0xb243ac69,
0xb3dda9db,0x32d0b032,0xa9db33dd,0x303232d0,0x33dd29db,0xb2d03032,0x29dbb3dd,0xb032b2d0,0xb3dda9db,0x32d0b032,0xa9db33dd,0x303232d0,0x33dd29db,0xb2d03032,0x29dbb3dd,0xb032b2d0,
0x327f2b4c,0xb0623081,0x30abb3ca,0xb2b1b29c,0xa92eb2cc,0xaa88b3dc,0xb3e53038,0x33d529f4,0xb0ab33ca,0x32b1329c,0x327f2b4c,0xb0623081,0x33e5b038,0xb3d5a9f4,0xa92eb2cc,0xaa88b3dc,
0xafcdac5d,0x2880b0ce,0xb2fc33b2,0x33ec3265,0xb2fc33b2,0x33ec3265,0x2fcd2c5d,0xa88030ce,0x2fcd2c5d,0xa88030ce,0x32fcb3b2,0xb3ecb265,0x32fcb3b2,0xb3ecb265,0xafcdac5d,0x2880b0ce,
0x24832d11,0x2cb13118,0x33fbb397,0xb3a6b22b,0x320baf26,0xaf80a614,0x313eb328,0xb311b3f7,0x33fbb397,0xb3a6b22b,0xa483ad11,0xacb1b118,0x313eb328,0xb311b3f7,0xb20b2f26,0x2f802614,
0xa1e30000,0x33fe3400,0xae70adc2,0x33533377,0xa867a5e2,0x33ed33f7,0xafc2af1b,0x32ff332b,0xab4ca9db,0x33ca33dd,0xb081b032,0x329c32d0,0xad11ac5d,0x339733b2,0xb118b0ce,0x322b3265,
0xaecc0000,0x333e3400,0x31c72dc2,0xb189b377,0xb3beb227,0x2c08311d,0x33f33395,0x2740ad1d,0xb27fb3dd,0xb0aba9db,0x306232d0,0x32b13032,0xa483afcd,0xb3fbb2fc,0xacb12880,0x33a633ec,
0xb1e90000,0x31643400,0xb374adc2,0x2dce3377,0xb0d3b3f7,0xb262a5e2,0xac69b32b,0xb3b1af1b,0x32cc29db,0xb038b3dd,0x33dc3032,0xa9f4b2d0,0x2f2633b2,0x33282c5d,0x26143265,0x33f730ce,
0xb3860000,0x2d703400,0x34002dc2,0x1d7fb377,0x300db11d,0xb2e6b227,0xb2432d1d,0x30fb3395,0x292e33dd,0x33e529db,0x2a88b2d0,0xb3d5b032,0xb20bb2fc,0xb13e2fcd,0x2f8033ec,0x3311a880,
0xb3fe0000,0xa1e33400,0xb353adc2,0xae703377,0x33ed25e2,0x2867b3f7,0x32ff2f1b,0x2fc2b32b,0xb3caa9db,0xab4c33dd,0xb29cb032,0xb08132d0,0x33972c5d,0x2d11b3b2,0x322b30ce,0x3118b265,
0xb33e0000,0xaecc3400,0x31892dc2,0x31c7b377,0x2c083227,0x33beb11d,0x2740b395,0xb3f32d1d,0x30abb3dd,0xb27fa9db,0xb2b132d0,0x30623032,0xb3fb2fcd,0x248332fc,0x33a6a880,0x2cb1b3ec,
0xb1640000,0xb1e93400,0xadceadc2,0xb3743377,0xb26233f7,0x30d325e2,0xb3b1332b,0x2c692f1b,0x303829db,0x32ccb3dd,0x29f43032,0x33dcb2d0,0x3328b3b2,0xaf26ac5d,0x33f7b265,0xa614b0ce,
0xad700000,0xb3863400,0x9d7f2dc2,0x3400b377,0xb2e6311d,0xb00d3227,0x30fbad1d,0x3243b395,0xb3e533dd,0x292e29db,0x33d5b2d0,0x2a88b032,0xb13e32fc,0x320bafcd,0x3311b3ec,0xaf802880,
0x21e30000,0xb3fe3400,0x2e70adc2,0xb3533377,0x2867a5e2,0xb3ed33f7,0x2fc2af1b,0xb2ff332b,0x2b4ca9db,0xb3ca33dd,0x3081b032,0xb29c32d0,0x2d11ac5d,0xb39733b2,0x3118b0ce,0xb22b3265,
0x2ecc0000,0xb33e3400,0xb1c72dc2,0x3189b377,0x33beb227,0xac08311d,0xb3f33395,0xa740ad1d,0x327fb3dd,0x30aba9db,0xb06232d0,0xb2b13032,0x2483afcd,0x33fbb2fc,0x2cb12880,0xb3a633ec,
0x31e90000,0xb1643400,0x3374adc2,0xadce3377,0x30d3b3f7,0x3262a5e2,0x2c69b32b,0x33b1af1b,0xb2cc29db,0x3038b3dd,0xb3dc3032,0x29f4b2d0,0xaf2633b2,0xb3282c5d,0xa6143265,0xb3f730ce,
0x33860000,0xad703400,0xb4002dc2,0x9d7fb377,0xb00db11d,0x32e6b227,0x32432d1d,0xb0fb3395,0xa92e33dd,0xb3e529db,0xaa88b2d0,0x33d5b032,0x320bb2fc,0x313e2fcd,0xaf8033ec,0xb311a880,
0x33fe0000,0x21e33400,0x3353adc2,0x2e703377,0xb3ed25e2,0xa867b3f7,0xb2ff2f1b,0xafc2b32b,0x33caa9db,0x2b4c33dd,0x329cb032,0x308132d0,0xb3972c5d,0xad11b3b2,0xb22b30ce,0xb118b265,
0x333e0000,0x2ecc3400,0xb1892dc2,0xb1c7b377,0xac083227,0xb3beb11d,0xa740b395,0x33f32d1d,0xb0abb3dd,0x327fa9db,0x32b132d0,0xb0623032,0x33fb2fcd,0xa48332fc,0xb3a6a880,0xacb1b3ec,
0x31640000,0x31e93400,0x2dceadc2,0x33743377,0x326233f7,0xb0d325e2,0x33b1332b,0xac692f1b,0xb03829db,0xb2ccb3dd,0xa9f43032,0xb3dcb2d0,0xb328b3b2,0x2f26ac5d,0xb3f7b265,0x2614b0ce,
0x2d700000,0x33863400,0x1d7f2dc2,0xb400b377,0x32e6311d,0x300d3227,0xb0fbad1d,0xb243b395,0x33e533dd,0xa92e29db,0xb3d5b2d0,0xaa88b032,0x313e32fc,0xb20bafcd,0xb311b3ec,0x2f802880,
0x0,0x34003400,0xb55f0000,0x35ed3800,0x0,0x34003400,0xb66db7f6,0xb4c42a46,0x0,0x34003400,0x341dae3e,0xb6ddb7d9,0x0,0x34003400,0x373b37a8,0x32d7b0a5,
0xb3feb15f,0x224831ed,0xb7fe0000,0x26483800,0xa248b1ed,0xb3feb15f,0x37eaaa46,0xacb2b7f6,0x33fe315f,0xa248b1ed,0xb7c32e3e,0x2fc637d9,0x224831ed,0x33fe315f,0x3788b0a5,0xb164b7a8,
0xa646b3f6,0xb3f62646,0xb5ed0000,0xb55f3800,0x264633f6,0x33f6a646,0xb4c437f6,0x366daa46,0xa646b3f6,0xb3f62646,0x36ddae3e,0x341db7d9,0x264633f6,0x33f6a646,0x32d7b7a8,0xb73b30a5,
0x33eab26d,0xa8b2b0c4,0xa6480000,0xb7fe3800,0xa8b2b0c4,0xb3ea326d,0xacb22a46,0xb7ea37f6,0xb3ea326d,0x28b230c4,0xafc62e3e,0xb7c337d9,0x28b230c4,0x33eab26d,0xb16430a5,0xb78837a8,
0x2a3eaa3e,0x33d9b3d9,0x355f0000,0xb5ed3800,0x2a3eaa3e,0x33d9b3d9,0x366db7f6,0x34c42a46,0x2a3eaa3e,0x33d9b3d9,0xb41dae3e,0x36ddb7d9,0x2a3eaa3e,0x33d9b3d9,0xb73b37a8,0xb2d7b0a5,
0xb3c3301d,0x2bc6b2dd,0x37fe0000,0xa6483800,0xabc632dd,0xb3c3301d,0xb7eaaa46,0x2cb2b7f6,0x33c3b01d,0xabc632dd,0x37c32e3e,0xafc637d9,0x2bc6b2dd,0x33c3b01d,0xb788b0a5,0x3164b7a8,
0xaca533a8,0xb3a8aca5,0x35ed0000,0x355f3800,0x2ca5b3a8,0x33a82ca5,0x34c437f6,0xb66daa46,0xaca533a8,0xb3a8aca5,0xb6ddae3e,0xb41db7d9,0x2ca5b3a8,0x33a82ca5,0xb2d7b7a8,0x373b30a5,
0x3388333b,0xad642ed7,0x26480000,0x37fe3800,0xad642ed7,0xb388b33b,0x2cb22a46,0x37ea37f6,0xb388b33b,0x2d64aed7,0x2fc62e3e,0x37c337d9,0x2d64aed7,0x3388333b,0x316430a5,0x378837a8,
};


__device__ __align__(1024) uint4 g_V[128 * 128 * 8];
__device__ __align__(1024) uint4 g_SIG[8 * 128 * 4];
__device__ __align__(1024) uint4 g_X[16 * 128 * 64];
__device__ __align__(1024) uint4 g_P[128 * 16 * 256];
__device__ __align__(1024) uint4 g_WT[8 * 16 * 1792];
__device__ __align__(1024) uint4 g_FT[128 * 1024];
__device__ unsigned g_wflag[2 * 8 * 32];
#define DEV __device__ __forceinline__
constexpr int STAGE = 28672;
constexpr int SPIN_MAX = 1 << 18;
constexpr uint32_t RTIME = 1100, WTIME = 2800, W1TIME = 5300, FTIME = 7250, FDELAY = 1500, DEPHASE = 350, IDLEWAIT = 1700, PGATE = 1700, PSTEP = 900;
DEV uint32_t smem_u32(const void* p) { return (uint32_t)__cvta_generic_to_shared(p); }
DEV void mbar_expect_tx(uint32_t bar, uint32_t bytes) { asm volatile("mbarrier.arrive.expect_tx.shared::cta.b64 _, [%0], %1;" :: "r"(bar), "r"(bytes) : "memory"); }
DEV void mbar_arrive_remote(uint32_t rbar) { asm volatile("mbarrier.arrive.shared::cluster.b64 _, [%0];" :: "r"(rbar) : "memory"); }
DEV void mbar_wait(uint32_t bar, uint32_t parity, int& bud) {
  asm volatile("{ .reg .pred p;\nW: mbarrier.try_wait.parity.shared::cta.b64 p, [%1], %2;\nadd.s32 %0, %0, -1;\nsetp.gt.and.s32 p, %0, 0, !p;\n@p bra W;\n}"
               : "+r"(bud) : "r"(bar), "r"(parity) : "memory");
}
DEV void mbar_wait_cl(uint32_t bar, uint32_t parity, int& bud) {
  asm volatile("{ .reg .pred p;\nW: mbarrier.try_wait.parity.acquire.cluster.shared::cta.b64 p, [%1], %2;\nadd.s32 %0, %0, -1;\nsetp.gt.and.s32 p, %0, 0, !p;\n@p bra W;\n}"
               : "+r"(bud) : "r"(bar), "r"(parity) : "memory");
}
DEV uint32_t mapa(uint32_t a, uint32_t r) { uint32_t o; asm("mapa.shared::cluster.u32 %0, %1, %2;" : "=r"(o) : "r"(a), "r"(r)); return o; }
DEV void bulk_load(uint32_t dst, const void* src, uint32_t bytes, uint32_t bar) {
  asm volatile("{ .reg .pred p; elect.sync _|p, 0xffffffff;\n@p mbarrier.arrive.expect_tx.shared::cta.b64 _, [%3], %2;\n"
               "@p cp.async.bulk.shared::cluster.global.mbarrier::complete_tx::bytes [%0], [%1], %2, [%3];\n}"
               :: "r"(dst), "l"(src), "r"(bytes), "r"(bar) : "memory");
}
DEV uint4 ldg_l2(const uint4* p) {
  uint4 v; asm volatile("ld.relaxed.gpu.global.v4.u32 {%0,%1,%2,%3}, [%4];" : "=r"(v.x), "=r"(v.y), "=r"(v.z), "=r"(v.w) : "l"(p) : "memory"); return v;
}
DEV void stg(uint4* p, uint4 v) { asm volatile("st.relaxed.gpu.global.v4.u32 [%0], {%1,%2,%3,%4};" :: "l"(p), "r"(v.x), "r"(v.y), "r"(v.z), "r"(v.w) : "memory"); }
DEV uint4 lds128(uint32_t a) { uint4 v; asm volatile("ld.shared.v4.u32 {%0,%1,%2,%3}, [%4];" : "=r"(v.x), "=r"(v.y), "=r"(v.z), "=r"(v.w) : "r"(a) : "memory"); return v; }
DEV void sts128(uint32_t a, uint4 v) { asm volatile("st.shared.v4.u32 [%0], {%1,%2,%3,%4};" :: "r"(a), "r"(v.x), "r"(v.y), "r"(v.z), "r"(v.w) : "memory"); }
DEV void lds64(uint32_t& x, uint32_t& y, uint32_t a) { asm volatile("ld.shared.v2.u32 {%0,%1}, [%2];" : "=r"(x), "=r"(y) : "r"(a) : "memory"); }
DEV uint32_t lds32(uint32_t a) { uint32_t v; asm volatile("ld.shared.u32 %0, [%1];" : "=r"(v) : "r"(a) : "memory"); return v; }
DEV void sts32(uint32_t a, uint32_t v) { asm volatile("st.shared.u32 [%0], %1;" :: "r"(a), "r"(v) : "memory"); }
DEV uint4 ldsm(uint32_t a) { uint4 v; asm volatile("ldmatrix.sync.aligned.m8n8.x4.shared.b16 {%0,%1,%2,%3}, [%4];" : "=r"(v.x), "=r"(v.y), "=r"(v.z), "=r"(v.w) : "r"(a) : "memory"); return v; }
DEV uint4 ldsm_t(uint32_t a) { uint4 v; asm volatile("ldmatrix.sync.aligned.m8n8.x4.trans.shared.b16 {%0,%1,%2,%3}, [%4];" : "=r"(v.x), "=r"(v.y), "=r"(v.z), "=r"(v.w) : "r"(a) : "memory"); return v; }
DEV void stsm(uint32_t a, uint2 x, uint2 y) { asm volatile("stmatrix.sync.aligned.m8n8.x4.shared.b16 [%0], {%1,%2,%3,%4};" :: "r"(a), "r"(x.x), "r"(x.y), "r"(y.x), "r"(y.y) : "memory"); }
DEV void stsm_t(uint32_t a, uint2 x, uint2 y) { asm volatile("stmatrix.sync.aligned.m8n8.x4.trans.shared.b16 [%0], {%1,%2,%3,%4};" :: "r"(a), "r"(x.x), "r"(x.y), "r"(y.x), "r"(y.y) : "memory"); }
DEV uint32_t pkh(float lo, float hi) { uint32_t r; asm("cvt.rn.f16x2.f32 %0, %1, %2;" : "=r"(r) : "f"(hi), "f"(lo)); return r; }
DEV uint32_t pkb(float lo, float hi) { uint32_t r; asm("cvt.rn.bf16x2.f32 %0, %1, %2;" : "=r"(r) : "f"(hi), "f"(lo)); return r; }
DEV uint32_t pkb_tag(float lo, float hi, uint32_t radd, uint32_t par) {
  return (__byte_perm(__float_as_uint(lo) + radd, pkb(lo, hi), 0x7632) & ~1u) | par;
}
DEV float blo(uint32_t w) { return __uint_as_float(w << 16); }
DEV float bhi(uint32_t w) { return __uint_as_float(w & 0xffff0000u); }
DEV float2 h2f(uint32_t w) { __half2 h = *reinterpret_cast<__half2*>(&w); return __half22float2(h); }
DEV uint32_t ng(uint32_t w) { return w ^ 0x80008000u; }
DEV float uf(uint32_t w) { return __uint_as_float(w); }
DEV uint32_t hmad(uint32_t a, uint32_t b, uint32_t c, uint32_t d) {
  uint32_t r; asm("{ .reg .b32 t; mul.rn.f16x2 t, %3, %4; fma.rn.f16x2 %0, %1, %2, t; }" : "=r"(r) : "r"(a), "r"(b), "r"(c), "r"(d)); return r;
}
DEV uint32_t hmsb(uint32_t a, uint32_t b, uint32_t c, uint32_t d) {
  uint32_t r; asm("{ .reg .b32 t; mul.rn.f16x2 t, %3, %4; neg.f16x2 t, t; fma.rn.f16x2 %0, %1, %2, t; }" : "=r"(r) : "r"(a), "r"(b), "r"(c), "r"(d)); return r;
}
DEV uint32_t badd4(uint32_t a, uint32_t b, uint32_t c, uint32_t d) {
  uint32_t r; asm("{ .reg .b32 x, y; add.rn.bf16x2 x, %1, %2; add.rn.bf16x2 y, %3, %4; add.rn.bf16x2 %0, x, y; }" : "=r"(r) : "r"(a), "r"(b), "r"(c), "r"(d)); return r;
}
DEV void mma0(float (&d)[4], uint4 a, uint32_t b0, uint32_t b1) {
  asm("mma.sync.aligned.m16n8k16.row.col.f32.f16.f16.f32 {%0,%1,%2,%3},{%4,%5,%6,%7},{%8,%9},{%10,%10,%10,%10};"
      : "=f"(d[0]), "=f"(d[1]), "=f"(d[2]), "=f"(d[3]) : "r"(a.x), "r"(a.y), "r"(a.z), "r"(a.w), "r"(b0), "r"(b1), "f"(0.f));
}
DEV void mma1(float (&d)[4], uint4 a, uint32_t b0, uint32_t b1) {
  asm("mma.sync.aligned.m16n8k16.row.col.f32.f16.f16.f32 {%0,%1,%2,%3},{%4,%5,%6,%7},{%8,%9},{%0,%1,%2,%3};"
      : "+f"(d[0]), "+f"(d[1]), "+f"(d[2]), "+f"(d[3]) : "r"(a.x), "r"(a.y), "r"(a.z), "r"(a.w), "r"(b0), "r"(b1));
}
DEV uint2 mmah(uint4 a, uint32_t b0, uint32_t b1, uint2 c = make_uint2(0u, 0u)) {
  uint2 d;
  asm("mma.sync.aligned.m16n8k16.row.col.f16.f16.f16.f16 {%0,%1},{%2,%3,%4,%5},{%6,%7},{%8,%9};"
      : "=r"(d.x), "=r"(d.y) : "r"(a.x), "r"(a.y), "r"(a.z), "r"(a.w), "r"(b0), "r"(b1), "r"(c.x), "r"(c.y));
  return d;
}
DEV uint4 cmul(uint2 yr, uint2 yi, uint4 w) { return make_uint4(hmsb(yr.x, w.x, yi.x, w.z), hmsb(yr.y, w.y, yi.y, w.w), hmad(yr.x, w.z, yi.x, w.x), hmad(yr.y, w.w, yi.y, w.y)); }
DEV void wg_fence() { asm volatile("wgmma.fence.sync.aligned;" ::: "memory"); }
DEV void wg_commit() { asm volatile("wgmma.commit_group.sync.aligned;" ::: "memory"); }
template <int N> DEV void wg_wait() { asm volatile("wgmma.wait_group.sync.aligned %0;" :: "n"(N) : "memory"); }
DEV uint64_t mkdesc(uint32_t lo) { return ((uint64_t)0x40000040u << 32) | lo; }
template <int N> DEV void pin(float* a) {
#pragma unroll
  for (int i = 0; i < N; i++) asm volatile("" : "+f"(a[i]) :: "memory");
}
DEV void cpy2(uint32_t& a, uint32_t& b) { asm volatile("prmt.b32 %0, %0, 0, 0x3210; prmt.b32 %1, %1, 0, 0x3210;" : "+r"(a), "+r"(b)); }
DEV void pin4(uint4& v) { asm volatile("" : "+r"(v.x), "+r"(v.y), "+r"(v.z), "+r"(v.w)); }
__device__ __forceinline__ void wgmma_n224(float* d, uint32_t a0, uint32_t a1, uint32_t a2, uint32_t a3, uint64_t descB, int scaleD) {
  asm volatile("{\n.reg .pred p;\nsetp.ne.b32 p, %117, 0;\n"
    "wgmma.mma_async.sync.aligned.m64n224k16.f32.bf16.bf16 "
    "{%0,%1,%2,%3,%4,%5,%6,%7,%8,%9,%10,%11,%12,%13,%14,%15,%16,%17,%18,%19,%20,%21,%22,%23,%24,%25,%26,%27,%28,%29,%30,%31,%32,%33,%34,%35,%36,%37,%38,%39,%40,%41,%42,%43,%44,%45,%46,%47,%48,%49,%50,%51,%52,%53,%54,%55,%56,%57,%58,%59,%60,%61,%62,%63,%64,%65,%66,%67,%68,%69,%70,%71,%72,%73,%74,%75,%76,%77,%78,%79,%80,%81,%82,%83,%84,%85,%86,%87,%88,%89,%90,%91,%92,%93,%94,%95,%96,%97,%98,%99,%100,%101,%102,%103,%104,%105,%106,%107,%108,%109,%110,%111}, "
    "{%112,%113,%114,%115}, %116, p, 1, 1, 0;\n}\n"
    : "+f"(d[0]),"+f"(d[1]),"+f"(d[2]),"+f"(d[3]),"+f"(d[4]),"+f"(d[5]),"+f"(d[6]),"+f"(d[7]),"+f"(d[8]),"+f"(d[9]),"+f"(d[10]),"+f"(d[11]),"+f"(d[12]),"+f"(d[13]),"+f"(d[14]),"+f"(d[15]),"+f"(d[16]),"+f"(d[17]),"+f"(d[18]),"+f"(d[19]),"+f"(d[20]),"+f"(d[21]),"+f"(d[22]),"+f"(d[23]),"+f"(d[24]),"+f"(d[25]),"+f"(d[26]),"+f"(d[27]),"+f"(d[28]),"+f"(d[29]),"+f"(d[30]),"+f"(d[31]),"+f"(d[32]),"+f"(d[33]),"+f"(d[34]),"+f"(d[35]),"+f"(d[36]),"+f"(d[37]),"+f"(d[38]),"+f"(d[39]),"+f"(d[40]),"+f"(d[41]),"+f"(d[42]),"+f"(d[43]),"+f"(d[44]),"+f"(d[45]),"+f"(d[46]),"+f"(d[47]),"+f"(d[48]),"+f"(d[49]),"+f"(d[50]),"+f"(d[51]),"+f"(d[52]),"+f"(d[53]),"+f"(d[54]),"+f"(d[55]),"+f"(d[56]),"+f"(d[57]),"+f"(d[58]),"+f"(d[59]),"+f"(d[60]),"+f"(d[61]),"+f"(d[62]),"+f"(d[63]),"+f"(d[64]),"+f"(d[65]),"+f"(d[66]),"+f"(d[67]),"+f"(d[68]),"+f"(d[69]),"+f"(d[70]),"+f"(d[71]),"+f"(d[72]),"+f"(d[73]),"+f"(d[74]),"+f"(d[75]),"+f"(d[76]),"+f"(d[77]),"+f"(d[78]),"+f"(d[79]),"+f"(d[80]),"+f"(d[81]),"+f"(d[82]),"+f"(d[83]),"+f"(d[84]),"+f"(d[85]),"+f"(d[86]),"+f"(d[87]),"+f"(d[88]),"+f"(d[89]),"+f"(d[90]),"+f"(d[91]),"+f"(d[92]),"+f"(d[93]),"+f"(d[94]),"+f"(d[95]),"+f"(d[96]),"+f"(d[97]),"+f"(d[98]),"+f"(d[99]),"+f"(d[100]),"+f"(d[101]),"+f"(d[102]),"+f"(d[103]),"+f"(d[104]),"+f"(d[105]),"+f"(d[106]),"+f"(d[107]),"+f"(d[108]),"+f"(d[109]),"+f"(d[110]),"+f"(d[111])
    : "r"(a0), "r"(a1), "r"(a2), "r"(a3), "l"(descB), "r"(scaleD));
}
__device__ __forceinline__ void wgmma_n64(float* d, uint32_t a0, uint32_t a1, uint32_t a2, uint32_t a3, uint64_t descB, int scaleD) {
  asm volatile("{\n.reg .pred p;\nsetp.ne.b32 p, %37, 0;\n"
    "wgmma.mma_async.sync.aligned.m64n64k16.f32.bf16.bf16 "
    "{%0,%1,%2,%3,%4,%5,%6,%7,%8,%9,%10,%11,%12,%13,%14,%15,%16,%17,%18,%19,%20,%21,%22,%23,%24,%25,%26,%27,%28,%29,%30,%31}, "
    "{%32,%33,%34,%35}, %36, p, 1, 1, 1;\n}\n"
    : "+f"(d[0]),"+f"(d[1]),"+f"(d[2]),"+f"(d[3]),"+f"(d[4]),"+f"(d[5]),"+f"(d[6]),"+f"(d[7]),"+f"(d[8]),"+f"(d[9]),"+f"(d[10]),"+f"(d[11]),"+f"(d[12]),"+f"(d[13]),"+f"(d[14]),"+f"(d[15]),"+f"(d[16]),"+f"(d[17]),"+f"(d[18]),"+f"(d[19]),"+f"(d[20]),"+f"(d[21]),"+f"(d[22]),"+f"(d[23]),"+f"(d[24]),"+f"(d[25]),"+f"(d[26]),"+f"(d[27]),"+f"(d[28]),"+f"(d[29]),"+f"(d[30]),"+f"(d[31])
    : "r"(a0), "r"(a1), "r"(a2), "r"(a3), "l"(descB), "r"(scaleD));
}

DEV void wsum2(float& a, float& b, int lane) {
  float k = (lane & 16) ? b : a, s = (lane & 16) ? a : b;
  k += __shfl_xor_sync(~0u, s, 16);
#pragma unroll
  for (int o = 8; o; o >>= 1) k += __shfl_xor_sync(~0u, k, o);
  a = __shfl_sync(~0u, k, 0); b = __shfl_sync(~0u, k, 16);
}
#define TAGS_BAD(d, par) ((((d)[0].x ^ (par)) | ((d)[1].x ^ (par)) | ((d)[2].x ^ (par)) | ((d)[3].x ^ (par))) & 1u)
template <int WIDE> DEV void refetch(uint32_t a, const char* gadj, int n, uint32_t par, int& bud) {
  do {
    if (__any_sync(~0u, ((lds32(a) ^ par) & 1u) & (--bud > 0))) {
      if (WIDE) sts128(a, ldg_l2(reinterpret_cast<const uint4*>(gadj + a)));
      else asm volatile("{ .reg .b64 t; ld.relaxed.gpu.global.b64 t, [%1]; st.shared.b64 [%0], t; }" :: "r"(a), "l"(gadj + a) : "memory");
    } else { a += WIDE ? 4096 : 2048; n--; }
  } while (n);
}
DEV float rsq_fast(float v) { float r; asm("rsqrt.approx.ftz.f32 %0, %1;" : "=f"(r) : "f"(v)); return r; }
#define FRESH_IDS() int tid = tid0; asm volatile("" : "+r"(tid)); const int lane = tid & 31, g = lane >> 2, q = lane & 3; (void)g; (void)q

struct Smem {
  static constexpr int FRAW = 0, WIN0 = 20480, WST0 = 36864, FST = 57344;
  static constexpr int SPILL = 3 * STAGE, COLT = SPILL, XO = SPILL, FIN = SPILL + 44032, EXT = SPILL + 57344, PIN = SPILL + 65536, XCH = SPILL + 65536,
                       WIN1 = SPILL + 81920, WST1 = SPILL + 98304, CX = SPILL + 114688, ROWT = SPILL + 131072, MISC = ROWT + 7168;
  static constexpr int FBAR = MISC, HFULL = MISC + 8, HFREE = MISC + 136, FULL = MISC + 200, RBAR = MISC + 240, RAWBAR = MISC + 248, CBAR = MISC + 256,
                       XOBAR = MISC + 264, ABAR = MISC + 280, PBAR = MISC + 344, WBAR = MISC + 376, EMPTY = MISC + 512,
                       MU = MISC + 576, SIG = MISC + 704, WMAX = MISC + 768, ZERO = MISC + 896, TOTAL = ZERO + 2048;
};
struct Maps { CUtensorMap m[9]; };
template <int ID, int N> DEV void bar_sync() { asm volatile("bar.sync %0, %1;" :: "n"(ID), "n"(N) : "memory"); }
template <int ID, int N> DEV void bar_arrive() { asm volatile("bar.arrive %0, %1;" :: "n"(ID), "n"(N) : "memory"); }
DEV void fence_async_smem() { asm volatile("fence.proxy.async.shared::cta;" ::: "memory"); }
DEV void tma_load(uint32_t dst, const CUtensorMap* m, int c0, int c1, uint32_t bar, uint32_t bytes) {
  asm volatile("{ .reg .pred p; elect.sync _|p, 0xffffffff;\n@p mbarrier.arrive.expect_tx.shared::cta.b64 _, [%2], %5;\n"
               "@p cp.async.bulk.tensor.2d.shared::cluster.global.mbarrier::complete_tx::bytes [%0], [%1, {%3, %4}], [%2];\n}"
               :: "r"(dst), "l"(m), "r"(bar), "r"(c0), "r"(c1), "r"(bytes) : "memory");
}
DEV void wait_until(uint32_t t0, uint32_t cycles) {
  asm volatile("{ .reg .pred p; .reg .u32 t;\nW: nanosleep.u32 40;\nmov.u32 t, %%clock;\nsub.u32 t, t, %0;\nsetp.lt.u32 p, t, %1;\n@p bra W;\n}" :: "r"(t0), "r"(cycles) : "memory");
}
DEV void spin(int cycles) { wait_until(clock(), cycles); }
DEV uint32_t ld_word(const void* p) { uint32_t t; asm volatile("ld.relaxed.gpu.global.u32 %0, [%1];" : "=r"(t) : "l"(p) : "memory"); return t; }
DEV void poll_tag(const void* p, uint32_t par, int& bud) {
  while (__any_sync(~0u, ((ld_word(p) ^ par) & 1u) & (--bud > 0))) {}
}
DEV uint32_t glu2(float g0, float g1, float u0, float u1) {
  uint32_t r;
  asm volatile("{ .reg .b32 a, b; cvt.rn.relu.bf16x2.f32 a, %2, %1; cvt.rn.bf16x2.f32 b, %4, %3; mul.rn.bf16x2 %0, a, b; }" : "=r"(r) : "f"(g0), "f"(g1), "f"(u0), "f"(u1));
  return r;
}
template <int K0, int K1> DEV void glu(const float* acc, uint4 (&h)[7]) {
#pragma unroll
  for (int k = K0; k < K1; k++) {
    const float* a = acc + 16 * k;
    h[k] = make_uint4(glu2(a[0], a[1], a[4], a[5]), glu2(a[2], a[3], a[6], a[7]), glu2(a[8], a[9], a[12], a[13]), glu2(a[10], a[11], a[14], a[15]));
  }
}
template <int K0, int K1> DEV void send_h(const uint4 (&h)[7], uint32_t rdst, uint32_t rbar) {
#pragma unroll
  for (int k = K0; k < K1; k++)
    asm volatile("st.async.shared::cluster.mbarrier::complete_tx::bytes.v4.u32 [%0], {%1,%2,%3,%4}, [%5];"
                 :: "r"(rdst + k * 4096), "r"(h[k].x), "r"(h[k].y), "r"(h[k].z), "r"(h[k].w), "r"(rbar) : "memory");
}
template <int K0, int K1> DEV void g2(float* acc, const uint4 (&h1)[7], const uint4 (&h2)[7], uint32_t lo, int accum = 1) {
#pragma unroll
  for (int k = K0; k < K1; k++) {
    const uint4& h = k < 7 ? h1[k < 7 ? k : 0] : h2[k < 7 ? 0 : k - 7];
    wgmma_n64(acc, h.x, h.y, h.z, h.w, mkdesc(lo + k * 128), k == 0 ? accum : 1);
  }
}
template <int V> DEV void store_piece(float* acc, uint4* dst, int off, uint32_t radd, uint32_t par) {
  float* a = acc + 8 * V;
  pin<8>(a);
  stg(reinterpret_cast<uint4*>(reinterpret_cast<uintptr_t>(dst) ^ ((V >> 1) * 160 + (V & 1) * 64)) + off, make_uint4(pkb_tag(a[0], a[1], radd, par), pkb(a[2], a[3]), pkb(a[4], a[5]), pkb(a[6], a[7])));
}

__global__ void __cluster_dims__(2, 1, 1) __launch_bounds__(384, 1)
fused_kernel(const __nv_bfloat16* __restrict__ x, const __nv_bfloat16* __restrict__ Wd,
             const __grid_constant__ Maps maps, __nv_bfloat16* __restrict__ out) {
  extern __shared__ uint8_t smem_raw[];
  const uint32_t sb = __shfl_sync(~0u, (smem_u32(smem_raw) + 1023) & ~1023u, 0);
  const int tid0 = threadIdx.x, w = __shfl_sync(~0u, tid0 >> 5, 0);
  const int cta = __shfl_sync(~0u, blockIdx.x, 0), e = cta >> 3, b = cta & 7;
  int bud = SPIN_MAX;
  if (w >= 8) {
    asm volatile("setmaxnreg.dec.sync.aligned.u32 40;");
    const int ht = tid0 - 256, lane = ht & 31;
    const uint32_t tstart = clock();
    uint4* const fbox = g_FT + ((cta >> 4) + (cta & 1) * 8 + (cta & 12) * 4 + (cta & 2) * 32) * 1024;
    const int bU = cta / 14, rem = cta - 14 * bU;
    asm volatile("{ .reg .pred p, q; .reg .u32 a; elect.sync _|p, 0xffffffff; mov.u32 a, %0;\n"
                 "L: @p mbarrier.init.shared::cta.b64 [a], 1;\n@p mbarrier.init.shared::cta.b64 [a+32], 1;\n@p mbarrier.init.shared::cta.b64 [a+64], 1;\n@p mbarrier.init.shared::cta.b64 [a+96], 1;\nadd.u32 a, a, 128;\nsetp.lt.u32 q, a, %1;\n@q bra L;\n@p mbarrier.init.shared::cta.b64 [a], 2;\n}"
                 :: "r"(sb + Smem::MISC + (w - 8) * 8), "r"(sb + Smem::EMPTY) : "memory");
    asm volatile("fence.mbarrier_init.release.cluster; barrier.cluster.arrive.relaxed.aligned; barrier.cluster.wait.aligned;" ::: "memory");
    if (w < 10) stg(g_X + (ht >> 1) * 4096 + cta * 32 + (ht & 1), make_uint4(0, 0, 0, 0));
    if (w == 10) bulk_load(sb + Smem::COLT, TAB_ALL + 5376, 44032, sb + Smem::CBAR);
    if (w == 9) bulk_load(sb + Smem::ROWT, TAB_ALL, 7168, sb + Smem::RBAR);
    wait_until(tstart, w == 11 ? WTIME : RTIME);
    if (w == 8)
      asm volatile("{ .reg .pred p; elect.sync _|p, 0xffffffff;\n@p mbarrier.arrive.expect_tx.shared::cta.b64 _, [%2], 16896;\n"
                   "@p cp.async.bulk.tensor.2d.shared::cluster.global.mbarrier::complete_tx::bytes [%0], [%1, {%3, %4}], [%2];\n"
                   "@p cp.async.bulk.tensor.2d.shared::cluster.global.mbarrier::complete_tx::bytes [%0+8448], [%5, {%3, %4}], [%2];\n}"
                   :: "r"(sb + Smem::FRAW), "l"(&maps.m[5]), "r"(sb + Smem::RAWBAR), "r"(((cta * 257 + 1) >> 3) * 4), "r"(0), "l"(&maps.m[6]) : "memory");
#define LOAD_W(p) asm volatile("{ .reg .pred p; elect.sync _|p, 0xffffffff;\n@p mbarrier.arrive.expect_tx.shared::cta.b64 _, [%2], 16384;\n" \
        "@p cp.async.bulk.tensor.4d.shared::cluster.global.mbarrier::complete_tx::bytes [%0], [%1, {%3, %4, %4, %4}], [%2];\n}" \
        :: "r"(sb + ((p) ? Smem::WIN1 : Smem::WIN0)), "l"(&maps.m[3 + (rem & 1)]), "r"(sb + Smem::WBAR + (p) * 8), "r"(224 * bU + 16 * (rem >> 1) + (p) * 112), "r"(0) : "memory")
    if (w == 11 && cta < 112) LOAD_W(0);
    {
      const int k0 = (w - 8) * 8 + (lane >> 2) + 1 - ((cta + 1) & 7);
      const uint32_t f0 = sb + Smem::FST + (lane & 3) * 16, fd = f0 + k0 * 64;
      const uint32_t d0 = k0 ? fd : f0 - 64, d7 = k0 == 32 ? f0 : fd + 14336, d8 = k0 ? fd + 16384 : f0;
      const uint32_t fa = sb + Smem::FRAW + (lane & 7) * 528 + ((lane >> 3) & 1) * 8448 + (lane >> 4) * 4224 + (w - 8) * 16;
      mbar_wait(sb + Smem::RAWBAR, 0, bud);
#pragma unroll
      for (int k0_ = 0; k0_ < 9; k0_ += 5) {
        uint4 f[5];
#pragma unroll
        for (int k = k0_; k < min(k0_ + 5, 9); k++) f[k - k0_] = ldsm_t(fa + k * 64);
#pragma unroll
        for (int k = k0_; k < min(k0_ + 5, 9); k++)
          sts128(k == 0 ? d0 : k == 7 ? d7 : k == 8 ? d8 : fd + k * 2048, make_uint4(max(f[k - k0_].x, 1u), f[k - k0_].y, f[k - k0_].z, f[k - k0_].w));
      }
      fence_async_smem();
      bar_sync<7, 128>();
      if (w == 8)
        asm volatile("{ .reg .pred p; elect.sync _|p, 0xffffffff;\n@p cp.async.bulk.tensor.3d.global.shared::cta.bulk_group [%0, {%2, %3, %3}], [%1];\ncp.async.bulk.commit_group;\n}"
                     :: "l"(&maps.m[8]), "r"(sb + Smem::FST), "r"((cta & 1) * 1024 + (cta & 14) * 64 + (cta >> 4) * 16), "r"(0) : "memory");
    }
    if (w == 11) {
      if (cta < 112) { wait_until(tstart, W1TIME); LOAD_W(1); }
#pragma unroll 1
      for (int p = 0; p < 2; p++) {
        asm volatile("bar.sync %0, 288;" :: "r"(9 + p) : "memory");
        if (cta < 112)
          asm volatile("{ .reg .pred p; elect.sync _|p, 0xffffffff;\n@p cp.async.bulk.tensor.3d.global.shared::cta.bulk_group [%0, {%2, %3, %4}], [%1];\n"
                       "cp.async.bulk.commit_group;\ncp.async.bulk.wait_group.read 0;\n}"
                       :: "l"(&maps.m[7]), "r"(sb + (p ? Smem::WST1 : Smem::WST0)), "r"((rem & 1) * 256), "r"(rem & ~1), "r"(bU * 16 + p * 8) : "memory");
        if (p) bar_arrive<13, 96>(); else bar_arrive<12, 64>();
        if (cta < 112)
          asm volatile("{ .reg .pred p; elect.sync _|p, 0xffffffff;\ncp.async.bulk.wait_group 0;\nfence.proxy.async.global;\nfence.acq_rel.gpu;\n"
                       "@p red.relaxed.gpu.global.add.u32 [%0], 1;\n}" :: "l"(g_wflag + (p * 8 + bU) * 32) : "memory");
      }
      mbar_wait(sb + Smem::ABAR + 56, 0, bud);
      asm volatile("{ .reg .pred p; elect.sync _|p, 0xffffffff; @p cp.async.bulk.prefetch.L2.global [%0], 14336; }" :: "l"(Wd + cta * 7168) : "memory");
#pragma unroll
      for (int k = 0; k < 4; k++) sts128(sb + Smem::ZERO + k * 512 + lane * 16, make_uint4(0, 0, 0, 0));
      fence_async_smem();
      __syncwarp();
#pragma unroll 1
      for (int k = 0; k < 32; k++) {
        asm volatile("{ .reg .pred p; elect.sync _|p, 0xffffffff; @p cp.async.bulk.global.shared::cta.bulk_group [%0], [%1], 2048; }"
                     :: "l"(g_P + (e * 32 + k) * 1024 + b * 128), "r"(sb + Smem::ZERO) : "memory");
        spin(60);
      }
      asm volatile("cp.async.bulk.commit_group; cp.async.bulk.wait_group 0; fence.proxy.async.global; fence.acq_rel.gpu;" ::: "memory");
      bar_arrive<14, 64>();
      mbar_wait(sb + Smem::ABAR + 56, 1, bud);
#pragma unroll 1
      for (int k = 0; k < 32; k++) stg(fbox + k * 32 + lane, make_uint4(0, 0, 0, 0));
      if (cta == 0) g_wflag[(lane & 15) * 32] = 0;
      return;
    }
    if (w == 10) wait_until(tstart, max((uint32_t)clock() - tstart + FDELAY, (uint32_t)FTIME));
#pragma unroll 1
    for (int layer = 0; layer < 2; layer++) {
      const uint32_t par = layer ^ 1;
      if (w == 10) {
        if (layer) { bar_sync<5, 288>(); mbar_wait(sb + Smem::PBAR + 24, 0, bud); bulk_load(sb + Smem::COLT, TAB_ALL + 5376, 44032, sb + Smem::CBAR); }
        bulk_load(sb + Smem::FIN, fbox, 16384, sb + Smem::FBAR);
      }
      if (w == 8) {
        if (layer) { mbar_wait(sb + Smem::PBAR + 24, 0, bud); spin(300); } else { bar_sync<12, 64>(); asm volatile("cp.async.bulk.wait_group.read 0;" ::: "memory"); }
        int slot = layer; uint32_t ph = par;
#pragma unroll 1
        for (int i = 0; i < 24; i++) {
          const int n = (i >> 1) == 9 ? i ^ 1 : i;
          if (!layer && !(n & 23)) {
            unsigned v;
            do { asm volatile("ld.acquire.gpu.global.u32 %0, [%1];" : "=r"(v) : "l"(g_wflag + (n + b) * 32) : "memory"); } while (__any_sync(~0u, (v < 14) & (--bud > 0)));
            asm volatile("fence.proxy.async.global;" ::: "memory");
          }
          if (!layer && n == 19) bar_sync<14, 64>();
          int sl = n - 16; uint32_t dst = Smem::EXT + (n - 19) * STAGE;
          if (n != 19 && n != 20) {
            sl = slot; dst = slot * STAGE;
            mbar_wait(sb + Smem::EMPTY + slot * 8, ph, bud);
            if (slot == 2) { slot = 0; ph ^= 1; } else slot++;
          }
          const bool dn = n >= 16;
          tma_load(sb + dst, &maps.m[dn], dn ? 256 * (b & 1) + 64 * ((0xfa44 >> (2 * n - 32)) & 3) : 0, 224 * (dn ? (b ^ ((0xac >> (n - 16)) & 1)) : b * 16 + n), sb + Smem::FULL + sl * 8, STAGE);
        }
      } else {
        uint32_t tmark = 0;
#pragma unroll 1
        for (int c = w - 9; c < 12; c += 2) {
          if (!(c & 10)) asm volatile("bar.sync %0, 320;" :: "r"(2 + (c >> 2)) : "memory");
          if ((c == 5 || c == 6) && !layer) bar_sync<13, 96>();
          if (c == 5) bulk_load(sb + Smem::ROWT, TAB_ALL + 1792 + layer * 1792, 7168, sb + Smem::RBAR);
          if ((c >> 1) == 4) {
            mbar_wait(sb + Smem::EMPTY + 24, layer, bud);
            asm volatile("{ .reg .pred p; elect.sync _|p, 0xffffffff;\n@p mbarrier.arrive.expect_tx.shared::cta.b64 _, [%2], 8192;\n"
                         "@p cp.async.bulk.tensor.3d.shared::cluster.global.mbarrier::complete_tx::bytes [%0], [%1, {%3, %4, %5}], [%2];\n}"
                         :: "r"(sb + Smem::XO + (c & 1) * 8192), "l"(&maps.m[2]), "r"(sb + Smem::XOBAR + (c & 1) * 8), "r"((b ^ (c & 1)) * 32 + (c & 1) * 512), "r"(e * 64), "r"(0) : "memory");
            tmark = clock();
          }
          if (c >= 10) wait_until(tmark, PGATE + (c - 10) * PSTEP);
          const uint4* src = c < 8 ? g_X + e * 8192 + c * 1024 : g_P + cta * 4096 + (c - 8) * 1024;
          poll_tag(src + (c < 8 ? lane * 32 : (lane >> 2) * 128 + (lane & 3) * 4), par, bud);

          bulk_load(sb + Smem::SPILL + (c < 8 ? c : c - 4) * 16384, src, 16384, sb + Smem::ABAR + c * 8);
        }
      }
    }
    return;
  }
  asm volatile("barrier.cluster.arrive.relaxed.aligned;" ::: "memory");
  asm volatile("setmaxnreg.inc.sync.aligned.u32 232;");
  float val[2][4][4];
  uint4 R[14];
  float xf[2][4][4] = {};
#define XO_ADDR(k) (((sb + Smem::XO + lane * 64 + (((w ^ (lane >> 1)) & 3) << 4) + (w >> 2) * 8) ^ (((k) & 1) << 5)) + (k) * 4096)
#define LOAD_ROWT() _Pragma("unroll") for (int i = 0; i < 14; i++) R[i] = lds128(sb + Smem::ROWT + i * 512 + lane * 16)
  {
    FRESH_IDS();
    uint2 xr[2][4];
    const uint2* xp = reinterpret_cast<const uint2*>(x + (256 * w + 16 * b + e) * 512 + 32 * q + 4 * g);
#pragma unroll
    for (int r = 0; r < 2; r++)
#pragma unroll
      for (int i = 0; i < 4; i++) asm volatile("ld.global.nc.v2.u32 {%0,%1}, [%2];" : "=r"(xr[r][i].x), "=r"(xr[r][i].y) : "l"(xp + r * 16384 + i * 32) : "memory");
#pragma unroll
    for (int i = 0; i < 14; i++)
      asm volatile("ld.global.nc.v4.u32 {%0,%1,%2,%3}, [%4];" : "=r"(R[i].x), "=r"(R[i].y), "=r"(R[i].z), "=r"(R[i].w) : "l"(reinterpret_cast<const uint4*>(TAB_ALL) + i * 32 + lane) : "memory");
#pragma unroll
    for (int r = 0; r < 2; r++)
#pragma unroll
      for (int i = 0; i < 4; i++) { val[r][i][0] = blo(xr[r][i].x); val[r][i][1] = bhi(xr[r][i].x); val[r][i][2] = blo(xr[r][i].y); val[r][i][3] = bhi(xr[r][i].y); }
    pin<32>(&val[0][0][0]);
  }
#define ACQUIRE(lo) do { mbar_wait(sb + Smem::FULL + slot * 8, phase, bud); lo = ((sb + slot * STAGE) >> 4) | 0x10000u; \
    if (slot == 2) { slot = 0; phase ^= 1; } else slot++; } while (0)
#define ACQUIRE_X(lo, i) do { mbar_wait(sb + Smem::FULL + 24 + (i) * 8, layer, bud); lo = ((sb + Smem::EXT + (i) * STAGE) >> 4) | 0x10000u; } while (0)
#define RELEASE_X() do { if ((tid & 127) == 0) asm volatile("mbarrier.arrive.shared::cta.b64 _, [%0];" :: "r"(sb + Smem::EMPTY + 24) : "memory"); } while (0)
#define RELEASE() do { if ((tid & 127) == 0) asm volatile("mbarrier.arrive.shared::cta.b64 _, [%0];" :: "r"(sb + Smem::EMPTY + rslot * 8) : "memory"); \
    rslot = rslot == 2 ? 0 : rslot + 1; } while (0)

#pragma unroll 1
  for (int it = 0; it < 4; it++) {
    const int layer = it == 3;
    const uint32_t par = layer ^ 1, radd = layer << 16;
    const bool wcol = it == 1 || it == 2;
    if (wcol && (w >= 4 || cta >= 112)) spin(cta < 112 ? DEPHASE : IDLEWAIT);
    if (!wcol || cta < 112) {
      FRESH_IDS();
      if (wcol) {
        mbar_wait(sb + Smem::WBAR - 8 + it * 8, 0, bud);
        const uint32_t wa = sb + (it == 1 ? Smem::WIN0 : Smem::WIN1) + q * 1024 + g * 32 + (((w ^ g) >> 2) << 4) + (w & 3) * 4;
#pragma unroll
        for (int i = 0; i < 4; i++)
#pragma unroll
          for (int t = 0; t < 4; t++) { const uint32_t v = lds32(wa + i * 4096 + t * 256); val[0][i][t] = blo(v); val[1][i][t] = bhi(v); }
      }
      float ev[2], od[2], z[2][4][4];
#pragma unroll
      for (int r = 0; r < 2; r++) {
        float mx = 0.f, my = 0.f, zr[2][4], zi[2][4];
        ev[r] = (val[r][0][0] + val[r][0][2]) + (val[r][1][0] + val[r][1][2]) + ((val[r][2][0] + val[r][2][2]) + (val[r][3][0] + val[r][3][2]));
        od[r] = (val[r][0][1] + val[r][0][3]) + (val[r][1][1] + val[r][1][3]) + ((val[r][2][1] + val[r][2][3]) + (val[r][3][1] + val[r][3][3]));
#pragma unroll
        for (int i = 0; i < 4; i++) { mx += val[r][i][0] * val[r][i][0]; my += val[r][i][1] * val[r][i][1]; mx += val[r][i][2] * val[r][i][2]; my += val[r][i][3] * val[r][i][3]; }
        const uint32_t ex = (__reduce_max_sync(~0u, __float_as_uint(mx + my)) + 0x800000u) >> 24;
        const float sc = __uint_as_float((193u - ex) << 23), isc = __uint_as_float((61u + ex) << 23);
        const float ms = __shfl_sync(~0u, ev[r] + od[r], 0) * (-0.0625f * sc);
#pragma unroll
        for (int t = 0; t < 4; t++) {
          uint32_t b0 = pkh(val[r][0][t] * sc + ms, val[r][1][t] * sc + ms), b1 = pkh(val[r][2][t] * sc + ms, val[r][3][t] * sc + ms);
          uint4 a = cmul(mmah(R[0], b0, b1), mmah(R[1], b0, b1), R[2 + t]);
#pragma unroll
          for (int u = 0; u < 2; u++) {
            const uint4 G = R[6 + 2 * t + u];
            if (t == 0) { mma0(zr[u], a, G.x, G.y); mma0(zi[u], a, G.z, G.w); }
            else        { mma1(zr[u], a, G.x, G.y); mma1(zi[u], a, G.z, G.w); }
          }
        }
#pragma unroll
        for (int k = 0; k < 4; k++)
#pragma unroll
          for (int h = 0; h < 2; h++) {
            z[r][k][2 * h] = zr[k >> 1][2 * h + (k & 1)] * isc + xf[r][k][2 * h]; z[r][k][2 * h + 1] = zi[k >> 1][2 * h + (k & 1)] * isc + xf[r][k][2 * h + 1];
          }
        wsum2(ev[r], od[r], lane);
        if (lane == 0) { z[r][0][0] = (ev[r] - od[r]) * 0.044194173824159216f + xf[r][0][0]; z[r][0][1] = 0.f; }
      }
      if (!wcol) {
        float ss[2];
#pragma unroll
        for (int r = 0; r < 2; r++) {
          float s0 = 0.f, s1 = 0.f;
#pragma unroll
          for (int k = 0; k < 4; k++) { s0 += z[r][k][0] * z[r][k][0]; s1 += z[r][k][1] * z[r][k][1]; s0 += z[r][k][2] * z[r][k][2]; s1 += z[r][k][3] * z[r][k][3]; }
          ss[r] = s0 + s1;
        }
        wsum2(ss[0], ss[1], lane);
        const float v0 = ss[0] * (1.f / 512) + 1e-5f, v1 = ss[1] * (1.f / 512) + 1e-5f, r0 = rsq_fast(v0), r1 = rsq_fast(v1);
#pragma unroll
        for (int k = 0; k < 4; k++)
          sts128(sb + Smem::XCH + k * 4096 + lane * 128 + ((w ^ ((lane & 1) * 4) ^ ((lane >> 1) & 3)) << 4),
                 make_uint4((pkh(z[0][k][0] * r0, z[1][k][0] * r1) & ~1u) | par, pkh(z[0][k][1] * r0, z[1][k][1] * r1),
                            (pkh(z[0][k][2] * r0, z[1][k][2] * r1) & ~1u) | par, pkh(z[0][k][3] * r0, z[1][k][3] * r1)));
        if (lane < 2) sts32(sb + Smem::SIG + ((w & 3) * 4 + 2 * (w >> 2) + lane) * 4, (__float_as_uint(lane ? v1 * r1 : v0 * r0) & ~1u) | par);
        bar_sync<1, 256>();
        uint4* vd = g_V + ((((tid >> 2) & 31) * 4 + (w >> 2)) * 128 + cta) * 4 + q;
        const uint32_t va = sb + Smem::XCH + (tid >> 2) * 128 + ((q ^ ((g & 1) * 4) ^ (g >> 1)) << 4);
        if (w == 7) stg(g_SIG + g * 512 + cta * 4 + q, lds128(sb + Smem::SIG + q * 16));
#pragma unroll
        for (int k = 0; k < 4; k++) {
          uint4 t;
          lds64(t.x, t.y, va + (k & 1) * 8192 + (k >> 1) * 8); lds64(t.z, t.w, (va ^ 64) + (k & 1) * 8192 + (k >> 1) * 8);
          stg(vd + (k & 1) * 1024 + (k >> 1) * 65536, t);
        }
        asm volatile("st.shared.v2.f32 [%0], {%1,%2};" :: "r"(sb + Smem::MU + layer * 64 + w * 8), "f"(ev[0] + od[0]), "f"(ev[1] + od[1]) : "memory");
      } else {
        const uint32_t dst = sb + (it == 1 ? Smem::WST0 : Smem::WST1) + (lane >> 3) * 2048 + w * 256 + (lane & 7) * 16;
#pragma unroll
        for (int r = 0; r < 2; r++)
#pragma unroll
          for (int h = 0; h < 2; h++)
            sts128(dst + r * 128 + h * 8192, make_uint4(pkb(z[r][0][2 * h], z[r][0][2 * h + 1]), pkb(z[r][1][2 * h], z[r][1][2 * h + 1]),
                                                      pkb(z[r][2][2 * h], z[r][2][2 * h + 1]), pkb(z[r][3][2 * h], z[r][3][2 * h + 1])));
        fence_async_smem();
      }
    }
    if (wcol) asm volatile("bar.arrive %0, 288;" :: "r"(8 + it) : "memory");
    if (it == 0) { asm volatile("barrier.cluster.wait.aligned;" ::: "memory"); continue; }
    if (it != 2) {
      FRESH_IDS();
      uint4 v[4], sg[2], fc[4];
      const uint4* vp = g_V + (cta * 128 + 16 * w) * 4 + lane;
#define VPTR(k) (vp + ((k) >> 1) * 65536 + ((k) & 1) * 32)
#pragma unroll
      for (int k = 0; k < 4; k++) { if (k < 2) v[k] = ldg_l2(VPTR(k)); fc[k] = make_uint4(0, 0, 0, 0); }
      const uint4* sgp = g_SIG + b * 512 + 64 * w + lane;
      mbar_wait(sb + Smem::CBAR, layer, bud);
      uint4 L[6], E[2][5], E1[2][2], G1[2], G2[2];
      const uint32_t ta = sb + Smem::COLT + lane * 16, te = ta + 3072 + w * 5120;
#define F_EXP() min(max(__reduce_max_sync(~0u, lds32(sb + Smem::WMAX + g * 4)) >> 23, 8u), 240u)
      uint32_t ex = lds32(sb + Smem::WMAX + g * 4);
#pragma unroll
      for (int ee = 0; ee < 2; ee++) { E[ee][0] = lds128(te + ee * 2560); E[ee][1] = lds128(te + ee * 2560 + 512); E[ee][4] = lds128(te + ee * 2560 + 2048); }
      L[0] = lds128(ta);
#pragma unroll
      for (int i = 2; i < 6; i++) L[i] = lds128(ta + i * 512);
#define LOAD_F() do { mbar_wait(sb + Smem::FBAR, layer, bud); _Pragma("unroll") for (int k = 0; k < 4; k++) fc[k] = lds128(sb + Smem::FIN + k * 4096 + tid * 16); } while (0)
      if (layer) LOAD_F();
      ex = min(max(__reduce_max_sync(~0u, ex) >> 23, 8u), 240u);
#pragma unroll
      for (int ee = 0; ee < 2; ee++) {
#pragma unroll
        for (int i = 0; i < 2; i++) { E1[ee][i] = make_uint4(E[ee][i].z, E[ee][i].w, ng(E[ee][i].x), ng(E[ee][i].y)); cpy2(E1[ee][i].x, E1[ee][i].y); }
        G1[ee] = make_uint4(E[ee][4].y, ng(E[ee][4].x), E[ee][4].x, E[ee][4].y);
        G2[ee] = make_uint4(E[ee][4].w, ng(E[ee][4].z), E[ee][4].z, E[ee][4].w);
        cpy2(G1[ee].x, G2[ee].x); cpy2(G2[ee].z, G2[ee].w);
      }
      uint32_t xa = sb + Smem::CX + lane * 256 + (((2 * w) ^ (lane & 7)) << 4);
      const int j1 = 2 * w + ((lane >> 3) & 1);
      uint32_t xc = sb + Smem::CX + (lane >> 4) * 4096 + j1 * 256 + (((lane ^ j1) & 7) << 4);
      uint4* xdst = g_X + 2 * w * 8192 + cta * 32 + (lane ^ (2 * (cta & 3)));
      uint32_t xd = xa + (((lane >> 3) & 1) - (lane >> 4)) * 2048;
#define V_WAIT(col) while (__any_sync(~0u, (((v[2 * (col)].x ^ par) | (v[2 * (col) + 1].x ^ par)) & 1u) & (--bud > 0))) { v[2 * (col)] = ldg_l2(VPTR(2 * (col))); v[2 * (col) + 1] = ldg_l2(VPTR(2 * (col) + 1)); }
      auto seg1 = [&](int col) {
#pragma unroll
        for (int ee = 0; ee < 2; ee++) {
          const uint4 t = v[2 * col + ee];
          uint4 a = cmul(mmah(E1[ee][1], t.z, t.w, mmah(E1[ee][0], t.x, t.y)), mmah(E[ee][1], t.z, t.w, mmah(E[ee][0], t.x, t.y)), L[0]);
          stsm((xa ^ (ee << 4)) + col * 8192, mmah(a, G1[ee].x, G1[ee].y), mmah(a, G1[ee].z, G1[ee].w));
        }
      };
      auto seg2 = [&](int col, uint4 a0, uint4 a1, float fs) {
        uint4 c[2];
        const uint4 fa = fc[2 * col], fb = fc[2 * col + 1];
#pragma unroll
        for (int u = 0; u < 2; u++) {
          uint2 dr = mmah(a1, L[4 + u].x, L[4 + u].y, mmah(a0, L[2 + u].x, L[2 + u].y)), di = mmah(a1, L[4 + u].z, L[4 + u].w, mmah(a0, L[2 + u].z, L[2 + u].w));
          const uint32_t f0 = u ? fa.z : fa.x, f1 = u ? fb.z : fb.x, f2 = u ? fa.w : fa.y, f3 = u ? fb.w : fb.y;
          uint4 t = cmul(dr, di, make_uint4(pkh(blo(f0) * fs, bhi(f0) * fs), pkh(blo(f1) * fs, bhi(f1) * fs), pkh(blo(f2) * fs, bhi(f2) * fs), pkh(blo(f3) * fs, bhi(f3) * fs)));
          c[u] = make_uint4(t.z, t.w, t.x, t.y);
        }
#pragma unroll
        for (int hb = 0; hb < 2; hb++)
          stsm_t(xc + col * 8192 + hb * 128, mmah(c[1], L[4 + hb].z, L[4 + hb].w, mmah(c[0], L[2 + hb].z, L[2 + hb].w)), mmah(c[1], L[4 + hb].x, L[4 + hb].y, mmah(c[0], L[2 + hb].x, L[2 + hb].y)));
      };
      auto seg3 = [&](int col, const uint4 (&y)[2], float fsi, float fa) {
#pragma unroll
        for (int ee = 0; ee < 2; ee++) {
          const uint2 d0 = mmah(G2[ee], y[ee].x, y[ee].y), d1 = mmah(G2[ee], y[ee].z, y[ee].w);
          const uint32_t r0 = hmad(d0.x, L[1].x, d0.y, L[1].z), i0 = hmsb(d0.y, L[1].x, d0.x, L[1].z), r1 = hmad(d1.x, L[1].y, d1.y, L[1].w), i1 = hmsb(d1.y, L[1].y, d1.x, L[1].w);
          const uint4 b0 = make_uint4(i0, ng(r0), r0, i0), b1 = make_uint4(i1, ng(r1), r1, i1), t = v[2 * col + ee];
          uint32_t o[4];
#pragma unroll
          for (int u = 0; u < 2; u++) {
            float d[4];
            mma0(d, b0, E[ee][2 + u].x, E[ee][2 + u].y); mma1(d, b1, E[ee][2 + u].z, E[ee][2 + u].w);
            const float2 vr = h2f(u ? t.z : t.x), vi = h2f(u ? t.w : t.y);
            const float s0 = uf(u ? sg[ee].z : sg[ee].x), s1 = uf(u ? sg[ee].w : sg[ee].y);
            o[2 * u] = pkb_tag(vr.x * s0 + d[0] * fsi, vi.x * s0 + d[2] * fa, radd, par);
            o[2 * u + 1] = pkb(vr.y * s1 + d[1] * fsi, vi.y * s1 + d[3] * fa);
          }
          stg(xdst + col * 4096 + ee * 8192, make_uint4(o[0], o[1], o[2], o[3]));
        }
      };
      V_WAIT(0);
      sg[0] = ldg_l2(sgp); sg[1] = ldg_l2(sgp + 32); v[2] = ldg_l2(VPTR(2)); v[3] = ldg_l2(VPTR(3));
      seg1(0);
      if (!layer) {
        LOAD_F();
        while (__any_sync(~0u, (min(min(fc[0].x, fc[1].x), min(fc[2].x, fc[3].x)) == 0) & (--bud > 0))) {
#pragma unroll
          for (int k = 0; k < 4; k++) fc[k] = ldg_l2(g_FT + ((cta >> 4) + (cta & 1) * 8 + (cta & 12) * 4 + (cta & 2) * 32) * 1024 + k * 256 + tid);
        }
        uint32_t m = 0;
#pragma unroll
        for (int k = 0; k < 4; k++) m = __vmaxu2(__vmaxu2(m, __vmaxu2(fc[k].x & 0x7fff7fffu, fc[k].y & 0x7fff7fffu)), __vmaxu2(fc[k].z & 0x7fff7fffu, fc[k].w & 0x7fff7fffu));
        sts32(sb + Smem::WMAX + w * 4, __reduce_max_sync(~0u, max(m, m << 16)));
      }
      bar_sync<8, 256>();
      uint4 a0 = ldsm_t(xc), a1 = ldsm_t(xc + 128), y[2];
      if (!layer) ex = F_EXP();
      L[1] = lds128(ta + 512);
#pragma unroll
      for (int ee = 0; ee < 2; ee++) { E[ee][2] = lds128(te + ee * 2560 + 1024); E[ee][3] = lds128(te + ee * 2560 + 1536); }
      const float fs = __uint_as_float((256u - ex) << 23), fsi = __uint_as_float((ex - 2u) << 23);
      seg2(0, a0, a1, fs);
      while (__any_sync(~0u, (((sg[0].x ^ par) | (sg[1].x ^ par)) & 1u) & (--bud > 0))) { sg[0] = ldg_l2(sgp); sg[1] = ldg_l2(sgp + 32); }
      bar_sync<8, 256>();
      y[0] = ldsm(xd); y[1] = ldsm(xd ^ 16);
      seg3(0, y, fsi, cta ? fsi : 0.f);
      bar_arrive<2, 320>();
      V_WAIT(1);
      seg1(1);
      bar_sync<8, 256>();
      a0 = ldsm_t(xc + 8192); a1 = ldsm_t(xc + 8320);
      seg2(1, a0, a1, fs);
      bar_sync<8, 256>();
      y[0] = ldsm(xd + 8192); y[1] = ldsm((xd ^ 16) + 8192);
      seg3(1, y, fsi, fsi);
      bar_arrive<3, 320>();
    }
    if (it == 1) {
      FRESH_IDS(); mbar_wait(sb + Smem::RBAR, 0, bud); LOAD_ROWT();
#pragma unroll
      for (int k = 0; k < 32; k++) (&xf[0][0][0])[k] = 0.f;
      continue;
    }
    uint4 xo[4];
    {
      FRESH_IDS();
      const uint32_t aoff = sb + Smem::SPILL + q * 512 + (((4 * w + (g >> 1)) ^ (2 * q)) << 4) + (g & 1) * 8;
      const uint32_t hoff = sb + Smem::SPILL + ((g & 4) + (g & 1) * 2 + ((g >> 1) & 1)) * 512 + ((w ^ (g & 1)) << 6) + q * 16;
#define LOAD_A(u, a) _Pragma("unroll") for (int k = 0; k < 4; k++) { lds64(A[u][k].x, A[u][k].y, (a) + k * 4096); lds64(A[u][k].z, A[u][k].w, (a) + k * 4096 + 2048); }
      const uint32_t raoff = mapa(hoff, (b & 1) ^ 1), rbar = mapa(sb + Smem::HFULL + w * 16, (b & 1) ^ 1);
      uint4 A[2][4], h1[7], h2[7];
      float acc[112], acc0[32];
#pragma unroll
      for (int k = 0; k < 7; k++) {
        const float* t = &val[0][0][0] + 4 * k;
        h1[k] = make_uint4(__float_as_uint(t[0]), __float_as_uint(t[1]), __float_as_uint(t[2]), __float_as_uint(t[3]));
      }
      wg_fence();
      wgmma_n224(acc, h1[0].x, h1[0].y, h1[0].z, h1[0].w, mkdesc((sb >> 4) | 0x10000u), 0);
      wg_commit();
      if (lane < 2) mbar_expect_tx(sb + Smem::HFULL + w * 16 + lane * 8, 7 * 512);
      uint32_t lo, phase = layer;
      int slot = layer, rslot = layer;
#pragma unroll 1
      for (int pass = 0; pass < 2; pass++) {
#pragma unroll 1
        for (int c2 = 0; c2 < 8; c2 += 2) {
#pragma unroll
          for (int u = 0; u < 2; u++) {
            const int c = c2 + u;
            if (pass == 0) mbar_wait(sb + Smem::ABAR + c * 8, layer, bud);
            uint32_t bad = 0;
#pragma unroll 1
            do {
              if (bad) refetch<0>(aoff + c * 16384, reinterpret_cast<const char*>(g_X + e * 8192) - (sb + Smem::SPILL), 8, par, bud);
              LOAD_A(u, aoff + c * 16384);
              mbar_wait(sb + Smem::FULL + slot * 8, phase, bud);
              if (pass == 0) bad = __any_sync(~0u, (TAGS_BAD(A[u], par) | (A[u][0].z ^ par) | (A[u][1].z ^ par) | (A[u][2].z ^ par) | (A[u][3].z ^ par)) & (bud > 0));
            } while (bad);
            lo = ((sb + slot * STAGE) >> 4) | 0x10000u;
            if (slot == 2) { slot = 0; phase ^= 1; } else slot++;
            wg_fence();
            wgmma_n224(acc, A[u][0].x, A[u][0].y, A[u][0].z, A[u][0].w, mkdesc(lo), u ? 1 : c2);
            wg_commit();
            wg_wait<1>();
            if (u | c2) RELEASE();
            if (pass == 1) {
              if (u == 0) {
                if (c2 == 2 && lane == 0) mbar_arrive_remote(rbar - Smem::HFULL + Smem::HFREE - w * 8);
                if (c2 == 4) send_h<2, 4>(h1, raoff, rbar);
                if (c2 == 6) send_h<6, 7>(h1, raoff, rbar);
              } else {
                if (c2 == 2) { mbar_wait(sb + Smem::HFREE + w * 8, layer, bud); send_h<0, 2>(h1, raoff, rbar); }
                if (c2 == 4) send_h<4, 6>(h1, raoff, rbar);
              }
            }
#pragma unroll
            for (int k = 1; k < 4; k++) wgmma_n224(acc, A[u][k].x, A[u][k].y, A[u][k].z, A[u][k].w, mkdesc(lo + k * 2), 1);
            wg_commit();
          }
        }
        if (pass == 0) {
          wg_wait<0>();
          RELEASE();
          pin<112>(acc);
          glu<0, 7>(acc, h1);
        }
      }
      float a1[32];
      float* const a2 = acc0; float* const a3 = a1;
      uint4 g1[7], g2r[7];
      uint32_t lo2;
      uint4* pdst = g_P + (e * 8 + w) * 4096 + b * 128 + ((g >> 1) + (g & 1) * 4) * 16 + (b & 1) * 4 + q;
#define G2_HEAD(a, x1, x2, accum) wg_fence(); g2<0, 2>(a, x1, x2, lo, accum); wg_commit(); wg_wait<1>()
#define G2_STORE(a, p, i) store_piece<0>(p, pdst, (i) * 1024, radd, par); g2<2, 5>(a, h1, h2, lo); store_piece<1>(p, pdst, (i) * 1024, radd, par); g2<5, 8>(a, h1, h2, lo); \
      store_piece<2>(p, pdst, (i) * 1024, radd, par); g2<8, 11>(a, h1, h2, lo); store_piece<3>(p, pdst, (i) * 1024, radd, par); g2<11, 14>(a, h1, h2, lo); wg_commit()
      ACQUIRE(lo);
      G2_HEAD(acc0, h1, h2, 0);
      RELEASE();
      pin<112>(acc);
      glu<0, 2>(acc, h2); g2<2, 3>(acc0, h1, h2, lo); glu<2, 3>(acc, h2); g2<3, 4>(acc0, h1, h2, lo); glu<3, 4>(acc, h2); g2<4, 5>(acc0, h1, h2, lo);
      mbar_wait_cl(sb + Smem::HFULL + w * 16, layer, bud);
      send_h<0, 2>(h2, raoff + 7 * 4096, rbar + 8);
      glu<4, 5>(acc, h2); g2<5, 6>(acc0, h1, h2, lo); glu<5, 6>(acc, h2); g2<6, 7>(acc0, h1, h2, lo); glu<6, 7>(acc, h2);
      wg_fence();
      g2<7, 11>(acc0, h1, h2, lo);
      send_h<2, 4>(h2, raoff + 7 * 4096, rbar + 8);
      g2<11, 14>(acc0, h1, h2, lo);
      wg_commit();
      ACQUIRE(lo);
      G2_HEAD(a1, h1, h2, 0);
      RELEASE();
      g2<2, 4>(a1, h1, h2, lo);
      send_h<4, 6>(h2, raoff + 7 * 4096, rbar + 8);
      g2<4, 10>(a1, h1, h2, lo);
      send_h<6, 7>(h2, raoff + 7 * 4096, rbar + 8);
#pragma unroll
      for (int k = 0; k < 7; k++) g1[k] = lds128(hoff + k * 4096);
      g2<10, 14>(a1, h1, h2, lo);
      wg_commit();
      ACQUIRE(lo);
      G2_HEAD(acc0, g1, g2r, 1);
      RELEASE();
      g2<2, 7>(acc0, g1, g2r, lo);
      ACQUIRE_X(lo2, 0);
      g2<0, 5>(a1, g1, g2r, lo2);
      mbar_wait_cl(sb + Smem::HFULL + w * 16 + 8, layer, bud);
#pragma unroll
      for (int k = 0; k < 7; k++) g2r[k] = lds128(hoff + (7 + k) * 4096);
      g2<5, 7>(a1, g1, g2r, lo2);
      wg_fence();
      g2<7, 14>(acc0, g1, g2r, lo);
      wg_commit();
      g2<7, 9>(a1, g1, g2r, lo2);
      wg_commit();
      wg_wait<1>();
      RELEASE();
      store_piece<0>(acc0, pdst, 0, radd, par); g2<9, 10>(a1, g1, g2r, lo2); store_piece<1>(acc0, pdst, 0, radd, par); g2<10, 11>(a1, g1, g2r, lo2);
      store_piece<2>(acc0, pdst, 0, radd, par); g2<11, 12>(a1, g1, g2r, lo2); store_piece<3>(acc0, pdst, 0, radd, par); g2<12, 14>(a1, g1, g2r, lo2);
      wg_commit();
      ACQUIRE_X(lo, 1);
      G2_HEAD(a2, h1, h2, 0);

      G2_STORE(a2, a1, 1);
      ACQUIRE(lo);
      G2_HEAD(a2, g1, g2r, 1);
      RELEASE_X();
      g2<2, 14>(a2, g1, g2r, lo);
      wg_commit();
      ACQUIRE(lo);
      G2_HEAD(a3, h1, h2, 0);
      RELEASE();
      G2_STORE(a3, a2, 2);
      ACQUIRE(lo);
      if (w >= 4) bar_sync<4, 256>();
      G2_HEAD(a3, g1, g2r, 1);
      RELEASE();
      g2<2, 8>(a3, g1, g2r, lo);
      mbar_wait(sb + Smem::XOBAR, layer, bud); mbar_wait(sb + Smem::XOBAR + 8, layer, bud);
#pragma unroll
      for (int k = 0; k < 4; k++) { lds64(xo[k].x, xo[k].y, XO_ADDR(k)); lds64(xo[k].z, xo[k].w, XO_ADDR(k) + 2048); }
      g2<8, 12>(a3, g1, g2r, lo);
      if (w < 4) bar_arrive<4, 256>();
      g2<12, 14>(a3, g1, g2r, lo);
      wg_commit();
      wg_wait<0>();
      RELEASE();
      store_piece<0>(a3, pdst, 3072, radd, par); store_piece<1>(a3, pdst, 3072, radd, par); store_piece<2>(a3, pdst, 3072, radd, par); store_piece<3>(a3, pdst, 3072, radd, par);
    }

    {
      FRESH_IDS();
      float r2[2], ir2[2], rsq[2];
      mbar_wait(sb + Smem::RBAR, par, bud);
      LOAD_ROWT();
#pragma unroll
      for (int k = 0; k < 4; k++) {
        pin4(xo[k]);
        xf[0][k][0] = blo(xo[k].x); xf[0][k][1] = bhi(xo[k].x); xf[1][k][0] = blo(xo[k].y); xf[1][k][1] = bhi(xo[k].y);
        xf[0][k][2] = blo(xo[k].z); xf[0][k][3] = bhi(xo[k].z); xf[1][k][2] = blo(xo[k].w); xf[1][k][3] = bhi(xo[k].w);
      }
#pragma unroll
      for (int r = 0; r < 2; r++) {
        float s0 = 0.f, s1 = 0.f;
#pragma unroll
        for (int k = 0; k < 4; k++) { s0 += xf[r][k][0] * xf[r][k][0]; s1 += xf[r][k][1] * xf[r][k][1]; s0 += xf[r][k][2] * xf[r][k][2]; s1 += xf[r][k][3] * xf[r][k][3]; }
        r2[r] = s0 + s1;
      }
      wsum2(r2[0], r2[1], lane);
#pragma unroll
      for (int r = 0; r < 2; r++) {
        r2[r] = r2[r] * (1.f / 512) + 1e-5f;
        rsq[r] = rsq_fast(r2[r]); ir2[r] = rsq[r] * rsq[r];
      }
      if (layer == 1) {
        float me[2], mo[2], sgm[2];
        uint32_t bb[2][2][2][2];
#pragma unroll
        for (int r = 0; r < 2; r++) {
          float nq = __shfl_sync(~0u, xf[r][0][0], 0) * 0.044194173824159216f, mu = (uf(lds32(sb + Smem::MU + w * 8 + r * 4)) + uf(lds32(sb + Smem::MU + 64 + w * 8 + r * 4))) * (1.f / 512);
          sgm[r] = r2[r] * rsq[r]; me[r] = mu + nq; mo[r] = mu - nq;
          if (lane == 0) xf[r][0][0] = 0.f;
#pragma unroll
          for (int u = 0; u < 2; u++)
#pragma unroll
            for (int h = 0; h < 2; h++) {
              bb[r][u][h][0] = pkh(xf[r][2 * u][2 * h] * rsq[r], xf[r][2 * u + 1][2 * h] * rsq[r]); bb[r][u][h][1] = pkh(xf[r][2 * u][2 * h + 1] * rsq[r], xf[r][2 * u + 1][2 * h + 1] * rsq[r]);
            }
        }
#pragma unroll
        for (int t = 0; t < 4; t++) {
          uint32_t ar[4], ai[4];
#pragma unroll
          for (int r = 0; r < 2; r++)
#pragma unroll
            for (int h = 0; h < 2; h++) {
              uint2 d = mmah(R[7 + 2 * t], bb[r][1][h][0], bb[r][1][h][1], mmah(R[6 + 2 * t], bb[r][0][h][0], bb[r][0][h][1]));
              uint32_t wr = h ? R[2 + t].y : R[2 + t].x, wi = h ? R[2 + t].w : R[2 + t].z;
              ar[r + 2 * h] = hmad(d.x, wr, d.y, wi); ai[r + 2 * h] = hmsb(d.y, wr, d.x, wi);
            }
#pragma unroll
          for (int up = 0; up < 2; up++) {
            float d[4];
            mma0(d, make_uint4(ar[0], ar[1], ar[2], ar[3]), up ? R[0].z : R[0].x, up ? R[0].w : R[0].y);
            mma1(d, make_uint4(ai[0], ai[1], ai[2], ai[3]), up ? R[1].z : R[1].x, up ? R[1].w : R[1].y);
#pragma unroll
            for (int c = 0; c < 4; c++) val[c >> 1][2 * up + (c & 1)][t] = d[c] * sgm[c >> 1] + ((t & 1) ? mo[c >> 1] : me[c >> 1]);
          }
        }
      }
      else {
#pragma unroll
        for (int i = 0; i < 32; i++) (&val[0][0][0])[i] = 0.f;
      }
      const int po = (q >> 1) * 128 + w * 16 + (q & 1) * 8 + (g ^ (2 * q));
      const uint32_t pa = sb + Smem::PIN + po * 16, ob = sb + Smem::XCH + w * 2048;
      uint32_t oa = ob + (q >> 1) * 528 + (q & 1) * 64 + (g >> 2) * 32 + (g & 3) * 4, ol = ob + (lane >> 3) * 512 + (((lane & 7) ^ ((lane >> 3) & 1)) << 4);
      uint4* op = reinterpret_cast<uint4*>(out) + (256 * w + 16 * b + e) * 64 + (lane >> 4) * 8192 + (lane & 8) * 4 + (lane & 7);
      asm volatile("" : "+r"(oa), "+r"(ol), "+l"(op));
#pragma unroll
      for (int part = 0; part < 2; part++) {
        const int i0 = part ? 3 : 0, i1 = part ? 4 : 3;
        uint4 pp[4][4];
#pragma unroll
        for (int i = i0; i < i1; i++) mbar_wait(sb + Smem::PBAR + i * 8, layer, bud);
        uint32_t bad = 0;
#pragma unroll 1
        do {
          if (bad) refetch<1>(pa + i0 * 16384, reinterpret_cast<const char*>(g_P + cta * 4096) - (sb + Smem::PIN), 4 * (i1 - i0), par, bud);
          bad = 0;
#pragma unroll
          for (int k = 4 * i0; k < 4 * i1; k++) { pp[k >> 2][k & 3] = lds128(pa + k * 4096); bad |= pp[k >> 2][k & 3].x ^ par; }
          bad = __any_sync(~0u, bad & (bud > 0));
        } while (bad);
        if (!part) { if (!layer) bar_arrive<5, 288>(); bar_sync<8, 256>(); }
#pragma unroll
        for (int i = i0; i < i1; i++) {
          const uint32_t s0 = badd4(pp[i][0].x, pp[i][1].x, pp[i][2].x, pp[i][3].x), s1 = badd4(pp[i][0].y, pp[i][1].y, pp[i][2].y, pp[i][3].y);
          const uint32_t s2 = badd4(pp[i][0].z, pp[i][1].z, pp[i][2].z, pp[i][3].z), s3 = badd4(pp[i][0].w, pp[i][1].w, pp[i][2].w, pp[i][3].w);
          val[0][i][0] += blo(s0) * ir2[0]; val[0][i][1] += bhi(s0) * ir2[0]; val[1][i][0] += blo(s1) * ir2[1]; val[1][i][1] += bhi(s1) * ir2[1];
          val[0][i][2] += blo(s2) * ir2[0]; val[0][i][3] += bhi(s2) * ir2[0]; val[1][i][2] += blo(s3) * ir2[1]; val[1][i][3] += bhi(s3) * ir2[1];
        }
        if (layer) {
#pragma unroll
          for (int i = i0; i < i1; i++)
#pragma unroll
            for (int r = 0; r < 2; r++) { sts32(oa + r * 1024 + i * 128, pkb(val[r][i][0], val[r][i][1])); sts32((oa ^ 16) + r * 1024 + i * 128, pkb(val[r][i][2], val[r][i][3])); }
          __syncwarp();
#pragma unroll
          for (int i = i0; i < i1; i++) stg(op + i * 8, lds128(ol + i * 128));
        }
        if (!part) { pin<32>(&val[0][0][0]); }
      }
    }
  }
}

extern "C" void kernel_launch(void* const* d_in, const int* in_sizes, int n_in, void* d_out, int out_size) {
  Maps maps;
  {
    typedef CUresult (*EncFn)(CUtensorMap*, CUtensorMapDataType, cuuint32_t, void*, const cuuint64_t*, const cuuint64_t*, const cuuint32_t*,
                              const cuuint32_t*, CUtensorMapInterleave, CUtensorMapSwizzle, CUtensorMapL2promotion, CUtensorMapFloatOOBfill);
    void* fn = nullptr;
    void* wt = nullptr;
    cudaDriverEntryPointQueryResult qr;
    cudaGetDriverEntryPoint("cuTensorMapEncodeTiled", &fn, cudaEnableDefault, &qr);
    cudaGetSymbolAddress(&wt, g_WT);
    void* xb = nullptr;
    cudaGetSymbolAddress(&xb, g_X);
    void* ft = nullptr;
    cudaGetSymbolAddress(&ft, g_FT);
    void* base[9] = {wt, d_in[6], xb, d_in[4], d_in[5], d_in[1], d_in[2], wt, ft};
    const int rank[9] = {2, 2, 3, 4, 4, 2, 2, 3, 3};
    const cuuint64_t dims[9][4] = {{64, 8 * 16 * 224}, {512, 1792}, {1024, 1024, 2}, {1792, 8, 4, 16}, {1792, 8, 4, 16}, {64 * 257, 16}, {64 * 257, 16}, {512, 14, 128}, {2048, 2, 128}};
    const cuuint64_t strides[9][3] = {{128}, {1024}, {2048, 512}, {4 * 3584, 3584, 32 * 3584}, {4 * 3584, 3584, 32 * 3584}, {256 * 257}, {256 * 257}, {2048, 28672}, {8192, 16384}};
    const cuuint32_t box[9][4] = {{64, 224}, {64, 224}, {32, 64, 2}, {16, 8, 4, 16}, {16, 8, 4, 16}, {132, 16}, {132, 16}, {256, 2, 8}, {16, 2, 128}}, es[4] = {1, 1, 1, 1};
    for (int i = 0; i < 9; i++)
      ((EncFn)fn)(&maps.m[i], i < 5 ? CU_TENSOR_MAP_DATA_TYPE_BFLOAT16 : CU_TENSOR_MAP_DATA_TYPE_UINT32, rank[i], base[i], dims[i], strides[i], box[i], es, CU_TENSOR_MAP_INTERLEAVE_NONE,
                  i < 2 ? CU_TENSOR_MAP_SWIZZLE_128B : i == 2 ? CU_TENSOR_MAP_SWIZZLE_64B : i < 5 ? CU_TENSOR_MAP_SWIZZLE_32B : CU_TENSOR_MAP_SWIZZLE_NONE,
                  i < 2 ? CU_TENSOR_MAP_L2_PROMOTION_L2_256B : CU_TENSOR_MAP_L2_PROMOTION_NONE, CU_TENSOR_MAP_FLOAT_OOB_FILL_NONE);
    cudaFuncSetAttribute(fused_kernel, cudaFuncAttributeMaxDynamicSharedMemorySize, Smem::TOTAL + 1024);
  }
  fused_kernel<<<128, 384, Smem::TOTAL + 1024, cudaStreamPerThread>>>((const __nv_bfloat16*)d_in[0], (const __nv_bfloat16*)d_in[6], maps, (__nv_bfloat16*)d_out);
}
```
